```python
import torch

def _softmax(x, axis=-1):
    return torch.softmax(x, dim=axis)
def _gelu(x):
    return torch.nn.functional.gelu(x, approximate="tanh")
def _silu(x):
    return torch.nn.functional.silu(x)
def _sigmoid(x):
    return torch.sigmoid(x)
def _layernorm(x, axis=-1, eps=1e-5):
    m = x.mean(dim=axis, keepdim=True)
    v = x.var(dim=axis, keepdim=True, unbiased=False)
    return (x - m) / torch.sqrt(v + eps)
def _scatter_add(tgt, idx, src, axis=0):
    return tgt.clone().index_add_(axis, idx, src)
def _segment_sum(src, seg, n):
    out = torch.zeros((n,) + src.shape[1:], dtype=src.dtype)
    return out.index_add_(0, seg, src)
def _pad(x, pw):
    flat = tuple(v for pair in reversed(pw) for v in pair)
    return torch.nn.functional.pad(x, flat)

kernel_name = 'interleave_layers__sliding_local_dilated__dense_activation_relu__prompt'

def setup_inputs():

    _w = (lambda a: (lambda t: t.to(torch.bfloat16) if t.is_floating_point() else t)(torch.as_tensor(a)))
    def _A_setup():
        B, S, D = 1, 2048, 640
        return {
            "x": _w((lambda *s: torch.randn(*s, dtype=torch.bfloat16) * 0.05)(B, S, D)),
            "wqkv": _w((lambda *s: torch.randn(*s, dtype=torch.bfloat16) * 0.05)(D, 3 * D)),
            "wo": _w((lambda *s: torch.randn(*s, dtype=torch.bfloat16) * 0.05)(D, D)),
        }
    _A_in = _A_setup()

    def _B_setup():
        B, S, D, Dff = 1, 2048, 640, 1728
        return {
            "x": _w((lambda *s: torch.randn(*s, dtype=torch.bfloat16) * 0.05)(B, S, D)),
            "w1": _w((lambda *s: torch.randn(*s, dtype=torch.bfloat16) * 0.05)(D, Dff)),
            "w2": _w((lambda *s: torch.randn(*s, dtype=torch.bfloat16) * 0.05)(Dff, D)),
        }
    _B_in = _B_setup()

    return {
        "A_x": _A_in["x"],
        "A_wqkv": _A_in["wqkv"],
        "A_wo": _A_in["wo"],
        "B_x": _B_in["x"],
        "B_w1": _B_in["w1"],
        "B_w2": _B_in["w2"],
    }

def reference(A_x, A_wqkv, A_wo, B_x, B_w1, B_w2):
    def _A_ref(x, wqkv, wo):
        B, S, D = x.shape
        H = 32; Dh = D // H
        W, dil = 8, 2
        qkv = (lambda x, *d: x.permute(*d))((x @ wqkv).reshape(B, S, 3, H, Dh), 2, 0, 3, 1, 4)
        q, k, v = qkv[0], qkv[1], qkv[2]
        scale = Dh ** -0.5
        pos = torch.arange(S)
        off = torch.arange(W) * dil
        idx = pos[:, None] - off[None, :]
        mask = idx >= 0
        idx_c = torch.where(mask, idx, 0).reshape(-1)
        kg = k[:, :, idx_c, :].reshape(B, H, S, W, Dh)
        vg = v[:, :, idx_c, :].reshape(B, H, S, W, Dh)
        logits = torch.einsum("bhsd,bhswd->bhsw", q, kg) * scale
        logits = torch.where(mask[None, None, :, :], logits, -1e9)
        attn = _softmax(logits, axis=-1)
        o = torch.einsum("bhsw,bhswd->bhsd", attn, vg)
        return (lambda x, *d: x.permute(*d))(o, 0, 2, 1, 3).reshape(B, S, D) @ wo

    def _B_ref(x, w1, w2):
        h = torch.einsum("bsd,df->bsf", x, w1)
        zero = torch.zeros_like(h)
        h = torch.maximum(h, zero)
        return torch.einsum("bsf,fd->bsd", h, w2)

    x = A_x
    x = x + _A_ref(_layernorm(x, axis=-1), A_wqkv, A_wo)
    x = x + _B_ref(_layernorm(x, axis=-1), B_w1, B_w2)
    x = x + _A_ref(_layernorm(x, axis=-1), A_wqkv, A_wo)
    x = x + _B_ref(_layernorm(x, axis=-1), B_w1, B_w2)
    return x
```

```cpp
#include <cuda_runtime.h>
#include <cuda.h>
#include <cuda_bf16.h>
#include <stdint.h>

namespace {

constexpr int D_ = 640, DFF_ = 1728;
constexpr int NCTA = 128;
#define NHL 4
constexpr uint32_t BSLOT = 16384, NBS = 8;
constexpr uint32_t ASLOT = 10752, ADATA = 10240;
constexpr uint32_t OFF_A = BSLOT * NBS;
constexpr uint32_t OFF_CS1 = OFF_A + 8 * ASLOT;
constexpr uint32_t OFF_CS3 = OFF_CS1 + 1024;
constexpr uint32_t OFF_CSP = OFF_CS3 + 1024;
constexpr uint32_t OFF_BAR = OFF_CSP + 512;
constexpr uint32_t BAR_FULLB = OFF_BAR, BAR_EMPTYB = BAR_FULLB + 8 * NBS;
constexpr uint32_t BAR_FULLA = BAR_EMPTYB + 8 * NBS, BAR_EMPTYA = BAR_FULLA + 64;
constexpr uint32_t BAR_LAND = BAR_EMPTYA + 64, BAR_PUSH = BAR_LAND + 16, BAR_CS = BAR_PUSH + 16;
constexpr uint32_t SMEM_USED = BAR_CS + 24;
constexpr uint32_t SMEM_BYTES = SMEM_USED + 1024;
constexpr uint32_t SPIN_LIMIT = 1u << 22;

__device__ __align__(128) uint8_t gX[32 * 8 * ASLOT];
__device__ __align__(128) uint8_t gO[32 * 8 * ADATA];
__device__ __align__(128) uint8_t gH[32 * 216 * 1024];
__device__ __align__(128) uint32_t gFlag[32 * 32];
__device__ __align__(128) uint4 gHalo[2 * 32 * 8 * 10 * 32];
__device__ __align__(128) uint2 gCS[2 * 8 * 256];
__device__ __align__(128) uint32_t gEpoch[NCTA];
#define STAMP(role, i) do {} while (0)

struct Params {
  CUtensorMap tq, to, t1, t2;
  const __nv_bfloat16 *x, *wqkv, *wo, *w1, *w2;
  __nv_bfloat16* out;
};

__device__ __forceinline__ uint32_t s2u(const void* p) { return (uint32_t)__cvta_generic_to_shared(p); }
__device__ __forceinline__ void mbar_init(uint32_t b, uint32_t c) { asm volatile("mbarrier.init.shared::cta.b64 [%0], %1;" ::"r"(b), "r"(c) : "memory"); }
__device__ __forceinline__ void mbar_expect(uint32_t b, uint32_t tx) { asm volatile("mbarrier.arrive.expect_tx.shared::cta.b64 _, [%0], %1;" ::"r"(b), "r"(tx) : "memory"); }
__device__ __forceinline__ void mbar_arrive(uint32_t b) { asm volatile("mbarrier.arrive.shared::cta.b64 _, [%0];" ::"r"(b) : "memory"); }
__device__ __forceinline__ void mbar_arrive_if(uint32_t b, bool p) {
  asm volatile("{.reg .pred p; setp.ne.u32 p, %1, 0; @p mbarrier.arrive.shared::cta.b64 _, [%0];}" ::"r"(b), "r"((uint32_t)p) : "memory"); }
__device__ __forceinline__ uint32_t mapa(uint32_t a, uint32_t cta) { uint32_t r; asm("mapa.shared::cluster.u32 %0, %1, %2;" : "=r"(r) : "r"(a), "r"(cta)); return r; }
__device__ __forceinline__ void mbar_arrive_remote(uint32_t rb) { asm volatile("mbarrier.arrive.release.cluster.shared::cluster.b64 _, [%0];" ::"r"(rb) : "memory"); }
__device__ __forceinline__ void mbar_wait(uint32_t b, uint32_t par) {
  asm volatile("{.reg .pred p; .reg .u32 n; mov.u32 n, 0;\n"
               "W: mbarrier.try_wait.parity.shared::cta.b64 p, [%0], %1;\n"
               "@p bra D;\n add.u32 n, n, 1; setp.lt.u32 p, n, %2; @p bra W; trap;\n D: }" ::"r"(b), "r"(par), "n"(SPIN_LIMIT) : "memory"); }
__device__ __forceinline__ void mbar_wait_cl(uint32_t b, uint32_t par) {
  asm volatile("{.reg .pred p; .reg .u32 n; mov.u32 n, 0;\n"
               "W: mbarrier.try_wait.parity.acquire.cluster.shared::cta.b64 p, [%0], %1;\n"
               "@p bra D;\n add.u32 n, n, 1; setp.lt.u32 p, n, %2; @p bra W; trap;\n D: }" ::"r"(b), "r"(par), "n"(SPIN_LIMIT) : "memory"); }
__device__ __forceinline__ void tma3d(uint32_t dst, const CUtensorMap* m, int c0, int c1, int c2, uint32_t bar) {
  asm volatile("cp.async.bulk.tensor.3d.shared::cluster.global.mbarrier::complete_tx::bytes [%0], [%1, {%3,%4,%5}], [%2];"
               ::"r"(dst), "l"(m), "r"(bar), "r"(c0), "r"(c1), "r"(c2) : "memory"); }
__device__ __forceinline__ void bulk_g2s(uint32_t dst, const void* src, uint32_t bytes, uint32_t bar) {
  asm volatile("cp.async.bulk.shared::cluster.global.mbarrier::complete_tx::bytes [%0], [%1], %2, [%3];" ::"r"(dst), "l"(src), "r"(bytes), "r"(bar) : "memory"); }
__device__ __forceinline__ void bulk_s2g(void* dst, uint32_t src, uint32_t bytes) {
  asm volatile("cp.async.bulk.global.shared::cta.bulk_group [%0], [%1], %2;" ::"l"(dst), "r"(src), "r"(bytes) : "memory"); }
__device__ __forceinline__ void bulk_s2s(uint32_t rdst, uint32_t src, uint32_t bytes, uint32_t rbar) {
  asm volatile("cp.async.bulk.shared::cluster.shared::cta.mbarrier::complete_tx::bytes [%0], [%1], %2, [%3];" ::"r"(rdst), "r"(src), "r"(bytes), "r"(rbar) : "memory"); }
__device__ __forceinline__ void l2_prefetch(const void* p, uint32_t bytes) { asm volatile("cp.async.bulk.prefetch.L2.global [%0], %1;" ::"l"(p), "r"(bytes) : "memory"); }
__device__ __forceinline__ void st_async4(uint32_t ra, float a, float b, float c, float d, uint32_t rbar) {
  asm volatile("st.async.weak.shared::cluster.mbarrier::complete_tx::bytes.v4.f32 [%0], {%1,%2,%3,%4}, [%5];" ::"r"(ra), "f"(a), "f"(b), "f"(c), "f"(d), "r"(rbar) : "memory"); }
__device__ __forceinline__ void fence_async_smem() { asm volatile("fence.proxy.async.shared::cta;" ::: "memory"); }
__device__ __forceinline__ void fence_async_glob() { asm volatile("fence.proxy.async.global;" ::: "memory"); }
__device__ __forceinline__ void bar_sync(int id, int n) { asm volatile("bar.sync %0, %1;" ::"r"(id), "r"(n) : "memory"); }
__device__ __forceinline__ void wg_fence() { asm volatile("wgmma.fence.sync.aligned;" ::: "memory"); }
__device__ __forceinline__ void wg_commit() { asm volatile("wgmma.commit_group.sync.aligned;" ::: "memory"); }
template <int N> __device__ __forceinline__ void wg_wait() { asm volatile("wgmma.wait_group.sync.aligned %0;" ::"n"(N) : "memory"); }
__device__ __forceinline__ void stsm4(uint32_t a, uint32_t r0, uint32_t r1, uint32_t r2, uint32_t r3) {
  asm volatile("stmatrix.sync.aligned.m8n8.x4.shared.b16 [%0], {%1,%2,%3,%4};" ::"r"(a), "r"(r0), "r"(r1), "r"(r2), "r"(r3) : "memory"); }
__device__ __forceinline__ void ldsm4(uint32_t a, uint32_t& r0, uint32_t& r1, uint32_t& r2, uint32_t& r3) {
  asm volatile("ldmatrix.sync.aligned.m8n8.x4.shared.b16 {%0,%1,%2,%3}, [%4];" : "=r"(r0), "=r"(r1), "=r"(r2), "=r"(r3) : "r"(a) : "memory"); }
__device__ __forceinline__ uint32_t movm(uint32_t a) { uint32_t d; asm volatile("movmatrix.sync.aligned.m8n8.trans.b16 %0, %1;" : "=r"(d) : "r"(a)); return d; }
__device__ __forceinline__ uint32_t pack2(float lo, float hi) { uint32_t r; asm("cvt.rn.bf16x2.f32 %0, %1, %2;" : "=r"(r) : "f"(hi), "f"(lo)); return r; }
__device__ __forceinline__ uint32_t pack2_relu(float lo, float hi) { uint32_t r; asm("cvt.rn.relu.bf16x2.f32 %0, %1, %2;" : "=r"(r) : "f"(hi), "f"(lo)); return r; }
__device__ __forceinline__ float blo(uint32_t v) { return __uint_as_float(v << 16); }
__device__ __forceinline__ float bhi(uint32_t v) { return __uint_as_float(v & 0xffff0000u); }
__device__ __forceinline__ float2 lds2f(uint32_t a) { float2 v; asm volatile("ld.shared.v2.f32 {%0,%1}, [%2];" : "=f"(v.x), "=f"(v.y) : "r"(a) : "memory"); return v; }
__device__ __forceinline__ float4 lds4f(uint32_t a) { float4 v; asm volatile("ld.shared.v4.f32 {%0,%1,%2,%3}, [%4];" : "=f"(v.x), "=f"(v.y), "=f"(v.z), "=f"(v.w) : "r"(a) : "memory"); return v; }
__device__ __forceinline__ uint4 lds4u(uint32_t a) { uint4 v; asm volatile("ld.shared.v4.u32 {%0,%1,%2,%3}, [%4];" : "=r"(v.x), "=r"(v.y), "=r"(v.z), "=r"(v.w) : "r"(a) : "memory"); return v; }
__device__ __forceinline__ uint2 lds2u(uint32_t a) { uint2 v; asm volatile("ld.shared.v2.u32 {%0,%1}, [%2];" : "=r"(v.x), "=r"(v.y) : "r"(a) : "memory"); return v; }
__device__ __forceinline__ void sts4u(uint32_t a, uint4 v) { asm volatile("st.shared.v4.u32 [%0], {%1,%2,%3,%4};" ::"r"(a), "r"(v.x), "r"(v.y), "r"(v.z), "r"(v.w) : "memory"); }
__device__ __forceinline__ void sts2u(uint32_t a, uint32_t x, uint32_t y) { asm volatile("st.shared.v2.u32 [%0], {%1,%2};" ::"r"(a), "r"(x), "r"(y) : "memory"); }
__device__ __forceinline__ void sts1f(uint32_t a, float x) { asm volatile("st.shared.f32 [%0], %1;" ::"r"(a), "f"(x) : "memory"); }
__device__ __forceinline__ float lds1f(uint32_t a) { float v; asm volatile("ld.shared.f32 %0, [%1];" : "=f"(v) : "r"(a) : "memory"); return v; }
__device__ __forceinline__ uint4 ldg_nc(const void* p) { uint4 v; asm volatile("ld.global.nc.L1::no_allocate.v4.u32 {%0,%1,%2,%3}, [%4];" : "=r"(v.x), "=r"(v.y), "=r"(v.z), "=r"(v.w) : "l"(p)); return v; }
__device__ __forceinline__ void st_ll2(void* p, uint32_t a, uint32_t b, uint32_t tag) {
  asm volatile("{.reg .b64 u, v; mov.b64 u, {%1,%3}; mov.b64 v, {%2,%3}; st.relaxed.gpu.global.v2.b64 [%0], {u, v};}" ::"l"(p), "r"(a), "r"(b), "r"(tag) : "memory"); }
__device__ __forceinline__ uint4 ld_ll2(const void* p) {
  uint4 v;
  asm volatile("{.reg .b64 u, v; ld.relaxed.gpu.global.v2.b64 {u, v}, [%4]; mov.b64 {%0,%1}, u; mov.b64 {%2,%3}, v;}" : "=r"(v.x), "=r"(v.y), "=r"(v.z), "=r"(v.w) : "l"(p) : "memory");
  return v; }
__device__ __forceinline__ void mma16816(float (&c)[4], uint32_t a0, uint32_t a1, uint32_t a2, uint32_t a3, uint32_t b0, uint32_t b1) {
  asm("mma.sync.aligned.m16n8k16.row.col.f32.bf16.bf16.f32 {%0,%1,%2,%3}, {%4,%5,%6,%7}, {%8,%9}, {%0,%1,%2,%3};"
      : "+f"(c[0]), "+f"(c[1]), "+f"(c[2]), "+f"(c[3]) : "r"(a0), "r"(a1), "r"(a2), "r"(a3), "r"(b0), "r"(b1)); }
__device__ __forceinline__ void mma1688(float (&c)[4], uint32_t a0, uint32_t a1, uint32_t b0) {
  asm("mma.sync.aligned.m16n8k8.row.col.f32.bf16.bf16.f32 {%0,%1,%2,%3}, {%4,%5}, {%6}, {%0,%1,%2,%3};"
      : "+f"(c[0]), "+f"(c[1]), "+f"(c[2]), "+f"(c[3]) : "r"(a0), "r"(a1), "r"(b0)); }
__device__ __forceinline__ float ex2(float x) { float r; asm("ex2.approx.ftz.f32 %0, %1;" : "=f"(r) : "f"(x)); return r; }

__device__ __forceinline__ void wgmma_ss0(float (&d)[120], uint64_t da, uint64_t db) {
  asm volatile("wgmma.mma_async.sync.aligned.m64n240k16.f32.bf16.bf16 {%0,%1,%2,%3,%4,%5,%6,%7,%8,%9,%10,%11,%12,%13,%14,%15,%16,%17,%18,%19,%20,%21,%22,%23,%24,%25,%26,%27,%28,%29,%30,%31,%32,%33,%34,%35,%36,%37,%38,%39,%40,%41,%42,%43,%44,%45,%46,%47,%48,%49,%50,%51,%52,%53,%54,%55,%56,%57,%58,%59,%60,%61,%62,%63,%64,%65,%66,%67,%68,%69,%70,%71,%72,%73,%74,%75,%76,%77,%78,%79,%80,%81,%82,%83,%84,%85,%86,%87,%88,%89,%90,%91,%92,%93,%94,%95,%96,%97,%98,%99,%100,%101,%102,%103,%104,%105,%106,%107,%108,%109,%110,%111,%112,%113,%114,%115,%116,%117,%118,%119}, %120, %121, 0, 1, 1, 0, 1;"
  : "=f"(d[0]),"=f"(d[1]),"=f"(d[2]),"=f"(d[3]),"=f"(d[4]),"=f"(d[5]),"=f"(d[6]),"=f"(d[7]),"=f"(d[8]),"=f"(d[9]),"=f"(d[10]),"=f"(d[11]),"=f"(d[12]),"=f"(d[13]),"=f"(d[14]),"=f"(d[15]),"=f"(d[16]),"=f"(d[17]),"=f"(d[18]),"=f"(d[19]),"=f"(d[20]),"=f"(d[21]),"=f"(d[22]),"=f"(d[23]),"=f"(d[24]),"=f"(d[25]),"=f"(d[26]),"=f"(d[27]),"=f"(d[28]),"=f"(d[29]),"=f"(d[30]),"=f"(d[31]),"=f"(d[32]),"=f"(d[33]),"=f"(d[34]),"=f"(d[35]),"=f"(d[36]),"=f"(d[37]),"=f"(d[38]),"=f"(d[39]),"=f"(d[40]),"=f"(d[41]),"=f"(d[42]),"=f"(d[43]),"=f"(d[44]),"=f"(d[45]),"=f"(d[46]),"=f"(d[47]),"=f"(d[48]),"=f"(d[49]),"=f"(d[50]),"=f"(d[51]),"=f"(d[52]),"=f"(d[53]),"=f"(d[54]),"=f"(d[55]),"=f"(d[56]),"=f"(d[57]),"=f"(d[58]),"=f"(d[59]),"=f"(d[60]),"=f"(d[61]),"=f"(d[62]),"=f"(d[63]),"=f"(d[64]),"=f"(d[65]),"=f"(d[66]),"=f"(d[67]),"=f"(d[68]),"=f"(d[69]),"=f"(d[70]),"=f"(d[71]),"=f"(d[72]),"=f"(d[73]),"=f"(d[74]),"=f"(d[75]),"=f"(d[76]),"=f"(d[77]),"=f"(d[78]),"=f"(d[79]),"=f"(d[80]),"=f"(d[81]),"=f"(d[82]),"=f"(d[83]),"=f"(d[84]),"=f"(d[85]),"=f"(d[86]),"=f"(d[87]),"=f"(d[88]),"=f"(d[89]),"=f"(d[90]),"=f"(d[91]),"=f"(d[92]),"=f"(d[93]),"=f"(d[94]),"=f"(d[95]),"=f"(d[96]),"=f"(d[97]),"=f"(d[98]),"=f"(d[99]),"=f"(d[100]),"=f"(d[101]),"=f"(d[102]),"=f"(d[103]),"=f"(d[104]),"=f"(d[105]),"=f"(d[106]),"=f"(d[107]),"=f"(d[108]),"=f"(d[109]),"=f"(d[110]),"=f"(d[111]),"=f"(d[112]),"=f"(d[113]),"=f"(d[114]),"=f"(d[115]),"=f"(d[116]),"=f"(d[117]),"=f"(d[118]),"=f"(d[119])
  : "l"(da), "l"(db));
}
__device__ __forceinline__ void wgmma_ss1(float (&d)[120], uint64_t da, uint64_t db) {
  asm volatile("wgmma.mma_async.sync.aligned.m64n240k16.f32.bf16.bf16 {%0,%1,%2,%3,%4,%5,%6,%7,%8,%9,%10,%11,%12,%13,%14,%15,%16,%17,%18,%19,%20,%21,%22,%23,%24,%25,%26,%27,%28,%29,%30,%31,%32,%33,%34,%35,%36,%37,%38,%39,%40,%41,%42,%43,%44,%45,%46,%47,%48,%49,%50,%51,%52,%53,%54,%55,%56,%57,%58,%59,%60,%61,%62,%63,%64,%65,%66,%67,%68,%69,%70,%71,%72,%73,%74,%75,%76,%77,%78,%79,%80,%81,%82,%83,%84,%85,%86,%87,%88,%89,%90,%91,%92,%93,%94,%95,%96,%97,%98,%99,%100,%101,%102,%103,%104,%105,%106,%107,%108,%109,%110,%111,%112,%113,%114,%115,%116,%117,%118,%119}, %120, %121, 1, 1, 1, 0, 1;"
  : "+f"(d[0]),"+f"(d[1]),"+f"(d[2]),"+f"(d[3]),"+f"(d[4]),"+f"(d[5]),"+f"(d[6]),"+f"(d[7]),"+f"(d[8]),"+f"(d[9]),"+f"(d[10]),"+f"(d[11]),"+f"(d[12]),"+f"(d[13]),"+f"(d[14]),"+f"(d[15]),"+f"(d[16]),"+f"(d[17]),"+f"(d[18]),"+f"(d[19]),"+f"(d[20]),"+f"(d[21]),"+f"(d[22]),"+f"(d[23]),"+f"(d[24]),"+f"(d[25]),"+f"(d[26]),"+f"(d[27]),"+f"(d[28]),"+f"(d[29]),"+f"(d[30]),"+f"(d[31]),"+f"(d[32]),"+f"(d[33]),"+f"(d[34]),"+f"(d[35]),"+f"(d[36]),"+f"(d[37]),"+f"(d[38]),"+f"(d[39]),"+f"(d[40]),"+f"(d[41]),"+f"(d[42]),"+f"(d[43]),"+f"(d[44]),"+f"(d[45]),"+f"(d[46]),"+f"(d[47]),"+f"(d[48]),"+f"(d[49]),"+f"(d[50]),"+f"(d[51]),"+f"(d[52]),"+f"(d[53]),"+f"(d[54]),"+f"(d[55]),"+f"(d[56]),"+f"(d[57]),"+f"(d[58]),"+f"(d[59]),"+f"(d[60]),"+f"(d[61]),"+f"(d[62]),"+f"(d[63]),"+f"(d[64]),"+f"(d[65]),"+f"(d[66]),"+f"(d[67]),"+f"(d[68]),"+f"(d[69]),"+f"(d[70]),"+f"(d[71]),"+f"(d[72]),"+f"(d[73]),"+f"(d[74]),"+f"(d[75]),"+f"(d[76]),"+f"(d[77]),"+f"(d[78]),"+f"(d[79]),"+f"(d[80]),"+f"(d[81]),"+f"(d[82]),"+f"(d[83]),"+f"(d[84]),"+f"(d[85]),"+f"(d[86]),"+f"(d[87]),"+f"(d[88]),"+f"(d[89]),"+f"(d[90]),"+f"(d[91]),"+f"(d[92]),"+f"(d[93]),"+f"(d[94]),"+f"(d[95]),"+f"(d[96]),"+f"(d[97]),"+f"(d[98]),"+f"(d[99]),"+f"(d[100]),"+f"(d[101]),"+f"(d[102]),"+f"(d[103]),"+f"(d[104]),"+f"(d[105]),"+f"(d[106]),"+f"(d[107]),"+f"(d[108]),"+f"(d[109]),"+f"(d[110]),"+f"(d[111]),"+f"(d[112]),"+f"(d[113]),"+f"(d[114]),"+f"(d[115]),"+f"(d[116]),"+f"(d[117]),"+f"(d[118]),"+f"(d[119])
  : "l"(da), "l"(db));
}

__device__ __forceinline__ void wgmma_ss0(float (&d)[112], uint64_t da, uint64_t db) {
  asm volatile("wgmma.mma_async.sync.aligned.m64n224k16.f32.bf16.bf16 {%0,%1,%2,%3,%4,%5,%6,%7,%8,%9,%10,%11,%12,%13,%14,%15,%16,%17,%18,%19,%20,%21,%22,%23,%24,%25,%26,%27,%28,%29,%30,%31,%32,%33,%34,%35,%36,%37,%38,%39,%40,%41,%42,%43,%44,%45,%46,%47,%48,%49,%50,%51,%52,%53,%54,%55,%56,%57,%58,%59,%60,%61,%62,%63,%64,%65,%66,%67,%68,%69,%70,%71,%72,%73,%74,%75,%76,%77,%78,%79,%80,%81,%82,%83,%84,%85,%86,%87,%88,%89,%90,%91,%92,%93,%94,%95,%96,%97,%98,%99,%100,%101,%102,%103,%104,%105,%106,%107,%108,%109,%110,%111}, %112, %113, 0, 1, 1, 0, 1;"
  : "=f"(d[0]),"=f"(d[1]),"=f"(d[2]),"=f"(d[3]),"=f"(d[4]),"=f"(d[5]),"=f"(d[6]),"=f"(d[7]),"=f"(d[8]),"=f"(d[9]),"=f"(d[10]),"=f"(d[11]),"=f"(d[12]),"=f"(d[13]),"=f"(d[14]),"=f"(d[15]),"=f"(d[16]),"=f"(d[17]),"=f"(d[18]),"=f"(d[19]),"=f"(d[20]),"=f"(d[21]),"=f"(d[22]),"=f"(d[23]),"=f"(d[24]),"=f"(d[25]),"=f"(d[26]),"=f"(d[27]),"=f"(d[28]),"=f"(d[29]),"=f"(d[30]),"=f"(d[31]),"=f"(d[32]),"=f"(d[33]),"=f"(d[34]),"=f"(d[35]),"=f"(d[36]),"=f"(d[37]),"=f"(d[38]),"=f"(d[39]),"=f"(d[40]),"=f"(d[41]),"=f"(d[42]),"=f"(d[43]),"=f"(d[44]),"=f"(d[45]),"=f"(d[46]),"=f"(d[47]),"=f"(d[48]),"=f"(d[49]),"=f"(d[50]),"=f"(d[51]),"=f"(d[52]),"=f"(d[53]),"=f"(d[54]),"=f"(d[55]),"=f"(d[56]),"=f"(d[57]),"=f"(d[58]),"=f"(d[59]),"=f"(d[60]),"=f"(d[61]),"=f"(d[62]),"=f"(d[63]),"=f"(d[64]),"=f"(d[65]),"=f"(d[66]),"=f"(d[67]),"=f"(d[68]),"=f"(d[69]),"=f"(d[70]),"=f"(d[71]),"=f"(d[72]),"=f"(d[73]),"=f"(d[74]),"=f"(d[75]),"=f"(d[76]),"=f"(d[77]),"=f"(d[78]),"=f"(d[79]),"=f"(d[80]),"=f"(d[81]),"=f"(d[82]),"=f"(d[83]),"=f"(d[84]),"=f"(d[85]),"=f"(d[86]),"=f"(d[87]),"=f"(d[88]),"=f"(d[89]),"=f"(d[90]),"=f"(d[91]),"=f"(d[92]),"=f"(d[93]),"=f"(d[94]),"=f"(d[95]),"=f"(d[96]),"=f"(d[97]),"=f"(d[98]),"=f"(d[99]),"=f"(d[100]),"=f"(d[101]),"=f"(d[102]),"=f"(d[103]),"=f"(d[104]),"=f"(d[105]),"=f"(d[106]),"=f"(d[107]),"=f"(d[108]),"=f"(d[109]),"=f"(d[110]),"=f"(d[111])
  : "l"(da), "l"(db));
}
__device__ __forceinline__ void wgmma_ss1(float (&d)[112], uint64_t da, uint64_t db) {
  asm volatile("wgmma.mma_async.sync.aligned.m64n224k16.f32.bf16.bf16 {%0,%1,%2,%3,%4,%5,%6,%7,%8,%9,%10,%11,%12,%13,%14,%15,%16,%17,%18,%19,%20,%21,%22,%23,%24,%25,%26,%27,%28,%29,%30,%31,%32,%33,%34,%35,%36,%37,%38,%39,%40,%41,%42,%43,%44,%45,%46,%47,%48,%49,%50,%51,%52,%53,%54,%55,%56,%57,%58,%59,%60,%61,%62,%63,%64,%65,%66,%67,%68,%69,%70,%71,%72,%73,%74,%75,%76,%77,%78,%79,%80,%81,%82,%83,%84,%85,%86,%87,%88,%89,%90,%91,%92,%93,%94,%95,%96,%97,%98,%99,%100,%101,%102,%103,%104,%105,%106,%107,%108,%109,%110,%111}, %112, %113, 1, 1, 1, 0, 1;"
  : "+f"(d[0]),"+f"(d[1]),"+f"(d[2]),"+f"(d[3]),"+f"(d[4]),"+f"(d[5]),"+f"(d[6]),"+f"(d[7]),"+f"(d[8]),"+f"(d[9]),"+f"(d[10]),"+f"(d[11]),"+f"(d[12]),"+f"(d[13]),"+f"(d[14]),"+f"(d[15]),"+f"(d[16]),"+f"(d[17]),"+f"(d[18]),"+f"(d[19]),"+f"(d[20]),"+f"(d[21]),"+f"(d[22]),"+f"(d[23]),"+f"(d[24]),"+f"(d[25]),"+f"(d[26]),"+f"(d[27]),"+f"(d[28]),"+f"(d[29]),"+f"(d[30]),"+f"(d[31]),"+f"(d[32]),"+f"(d[33]),"+f"(d[34]),"+f"(d[35]),"+f"(d[36]),"+f"(d[37]),"+f"(d[38]),"+f"(d[39]),"+f"(d[40]),"+f"(d[41]),"+f"(d[42]),"+f"(d[43]),"+f"(d[44]),"+f"(d[45]),"+f"(d[46]),"+f"(d[47]),"+f"(d[48]),"+f"(d[49]),"+f"(d[50]),"+f"(d[51]),"+f"(d[52]),"+f"(d[53]),"+f"(d[54]),"+f"(d[55]),"+f"(d[56]),"+f"(d[57]),"+f"(d[58]),"+f"(d[59]),"+f"(d[60]),"+f"(d[61]),"+f"(d[62]),"+f"(d[63]),"+f"(d[64]),"+f"(d[65]),"+f"(d[66]),"+f"(d[67]),"+f"(d[68]),"+f"(d[69]),"+f"(d[70]),"+f"(d[71]),"+f"(d[72]),"+f"(d[73]),"+f"(d[74]),"+f"(d[75]),"+f"(d[76]),"+f"(d[77]),"+f"(d[78]),"+f"(d[79]),"+f"(d[80]),"+f"(d[81]),"+f"(d[82]),"+f"(d[83]),"+f"(d[84]),"+f"(d[85]),"+f"(d[86]),"+f"(d[87]),"+f"(d[88]),"+f"(d[89]),"+f"(d[90]),"+f"(d[91]),"+f"(d[92]),"+f"(d[93]),"+f"(d[94]),"+f"(d[95]),"+f"(d[96]),"+f"(d[97]),"+f"(d[98]),"+f"(d[99]),"+f"(d[100]),"+f"(d[101]),"+f"(d[102]),"+f"(d[103]),"+f"(d[104]),"+f"(d[105]),"+f"(d[106]),"+f"(d[107]),"+f"(d[108]),"+f"(d[109]),"+f"(d[110]),"+f"(d[111])
  : "l"(da), "l"(db));
}

__device__ __forceinline__ void wgmma_ss0(float (&d)[80], uint64_t da, uint64_t db) {
  asm volatile("wgmma.mma_async.sync.aligned.m64n160k16.f32.bf16.bf16 {%0,%1,%2,%3,%4,%5,%6,%7,%8,%9,%10,%11,%12,%13,%14,%15,%16,%17,%18,%19,%20,%21,%22,%23,%24,%25,%26,%27,%28,%29,%30,%31,%32,%33,%34,%35,%36,%37,%38,%39,%40,%41,%42,%43,%44,%45,%46,%47,%48,%49,%50,%51,%52,%53,%54,%55,%56,%57,%58,%59,%60,%61,%62,%63,%64,%65,%66,%67,%68,%69,%70,%71,%72,%73,%74,%75,%76,%77,%78,%79}, %80, %81, 0, 1, 1, 0, 1;"
  : "=f"(d[0]),"=f"(d[1]),"=f"(d[2]),"=f"(d[3]),"=f"(d[4]),"=f"(d[5]),"=f"(d[6]),"=f"(d[7]),"=f"(d[8]),"=f"(d[9]),"=f"(d[10]),"=f"(d[11]),"=f"(d[12]),"=f"(d[13]),"=f"(d[14]),"=f"(d[15]),"=f"(d[16]),"=f"(d[17]),"=f"(d[18]),"=f"(d[19]),"=f"(d[20]),"=f"(d[21]),"=f"(d[22]),"=f"(d[23]),"=f"(d[24]),"=f"(d[25]),"=f"(d[26]),"=f"(d[27]),"=f"(d[28]),"=f"(d[29]),"=f"(d[30]),"=f"(d[31]),"=f"(d[32]),"=f"(d[33]),"=f"(d[34]),"=f"(d[35]),"=f"(d[36]),"=f"(d[37]),"=f"(d[38]),"=f"(d[39]),"=f"(d[40]),"=f"(d[41]),"=f"(d[42]),"=f"(d[43]),"=f"(d[44]),"=f"(d[45]),"=f"(d[46]),"=f"(d[47]),"=f"(d[48]),"=f"(d[49]),"=f"(d[50]),"=f"(d[51]),"=f"(d[52]),"=f"(d[53]),"=f"(d[54]),"=f"(d[55]),"=f"(d[56]),"=f"(d[57]),"=f"(d[58]),"=f"(d[59]),"=f"(d[60]),"=f"(d[61]),"=f"(d[62]),"=f"(d[63]),"=f"(d[64]),"=f"(d[65]),"=f"(d[66]),"=f"(d[67]),"=f"(d[68]),"=f"(d[69]),"=f"(d[70]),"=f"(d[71]),"=f"(d[72]),"=f"(d[73]),"=f"(d[74]),"=f"(d[75]),"=f"(d[76]),"=f"(d[77]),"=f"(d[78]),"=f"(d[79])
  : "l"(da), "l"(db));
}
__device__ __forceinline__ void wgmma_ss1(float (&d)[80], uint64_t da, uint64_t db) {
  asm volatile("wgmma.mma_async.sync.aligned.m64n160k16.f32.bf16.bf16 {%0,%1,%2,%3,%4,%5,%6,%7,%8,%9,%10,%11,%12,%13,%14,%15,%16,%17,%18,%19,%20,%21,%22,%23,%24,%25,%26,%27,%28,%29,%30,%31,%32,%33,%34,%35,%36,%37,%38,%39,%40,%41,%42,%43,%44,%45,%46,%47,%48,%49,%50,%51,%52,%53,%54,%55,%56,%57,%58,%59,%60,%61,%62,%63,%64,%65,%66,%67,%68,%69,%70,%71,%72,%73,%74,%75,%76,%77,%78,%79}, %80, %81, 1, 1, 1, 0, 1;"
  : "+f"(d[0]),"+f"(d[1]),"+f"(d[2]),"+f"(d[3]),"+f"(d[4]),"+f"(d[5]),"+f"(d[6]),"+f"(d[7]),"+f"(d[8]),"+f"(d[9]),"+f"(d[10]),"+f"(d[11]),"+f"(d[12]),"+f"(d[13]),"+f"(d[14]),"+f"(d[15]),"+f"(d[16]),"+f"(d[17]),"+f"(d[18]),"+f"(d[19]),"+f"(d[20]),"+f"(d[21]),"+f"(d[22]),"+f"(d[23]),"+f"(d[24]),"+f"(d[25]),"+f"(d[26]),"+f"(d[27]),"+f"(d[28]),"+f"(d[29]),"+f"(d[30]),"+f"(d[31]),"+f"(d[32]),"+f"(d[33]),"+f"(d[34]),"+f"(d[35]),"+f"(d[36]),"+f"(d[37]),"+f"(d[38]),"+f"(d[39]),"+f"(d[40]),"+f"(d[41]),"+f"(d[42]),"+f"(d[43]),"+f"(d[44]),"+f"(d[45]),"+f"(d[46]),"+f"(d[47]),"+f"(d[48]),"+f"(d[49]),"+f"(d[50]),"+f"(d[51]),"+f"(d[52]),"+f"(d[53]),"+f"(d[54]),"+f"(d[55]),"+f"(d[56]),"+f"(d[57]),"+f"(d[58]),"+f"(d[59]),"+f"(d[60]),"+f"(d[61]),"+f"(d[62]),"+f"(d[63]),"+f"(d[64]),"+f"(d[65]),"+f"(d[66]),"+f"(d[67]),"+f"(d[68]),"+f"(d[69]),"+f"(d[70]),"+f"(d[71]),"+f"(d[72]),"+f"(d[73]),"+f"(d[74]),"+f"(d[75]),"+f"(d[76]),"+f"(d[77]),"+f"(d[78]),"+f"(d[79])
  : "l"(da), "l"(db));
}

__device__ __forceinline__ int h_start(int sl) { return sl < 7 ? 224 * sl : 1536; }
__device__ __forceinline__ uint64_t lens_w2(int j) {
  uint64_t l = 0;
#pragma unroll
  for (int c = 0; c < 4; c++) { int sl = j ^ (2 * c); l |= (uint64_t)(0x055 | ((sl < 6 ? 4 : 2) << 8)) << (12 * c); }
  return l; }

__device__ __forceinline__ uint32_t enc(uint32_t a) { return (a & 0x3FFFF) >> 4; }

struct Ctx {
  uint32_t sb;
  uint32_t abase;
  uint32_t fulla, emptya;
  uint32_t an, bn;
  int lane, wi;
};
struct Stats { float c0, a0, m0, c1, a1, m1; };

template <int N, int SPS, bool STATS>
__device__ __forceinline__ void mainloop(float (&acc)[N / 2], Ctx& c, int nst, bool tail, uint64_t lens, Stats& st) {
  constexpr uint32_t SLAB = (SPS == 2) ? 8192 : 5120;
  constexpr uint64_t DESC_A = ((uint64_t)(1024 >> 4) << 16) | ((uint64_t)(128 >> 4) << 32);
  constexpr uint64_t DESC_B = (N == 240) ? (((uint64_t)(2048 >> 4) << 16) | ((uint64_t)(1024 >> 4) << 32) | (1ull << 62))
                                         : (((uint64_t)(1024 >> 4) << 16) | ((uint64_t)(512 >> 4) << 32) | (2ull << 62));
  uint32_t an = c.an, arel = c.an, afin = c.an, bn = c.bn;
  const bool el = c.lane == 0;
  const uint32_t strow = ADATA + (uint32_t)(c.wi * 16 + (c.lane >> 2)) * 8;
  uint32_t acur = c.abase + (an & 3) * ASLOT;
  mbar_wait(c.fulla + (an & 3) * 8, (an >> 2) & 1);
  {
    const uint32_t bs = c.sb + (bn & (NBS - 1)) * BSLOT;
    mbar_wait(c.sb + BAR_FULLB + (bn & (NBS - 1)) * 8, (bn / NBS) & 1);
    if (N == 240) fence_async_smem();
    wg_fence();
    wgmma_ss0(acc, DESC_A | enc(acur), DESC_B | enc(bs));
    wgmma_ss1(acc, DESC_A | enc(acur + 2048), DESC_B | enc(bs + SLAB));
    wg_commit();
  }
  if (STATS) {
    float2 s0 = lds2f(acur + strow), s1 = lds2f(acur + strow + 64);
    st.c0 = s0.x; st.c1 = s1.x; st.a0 = st.a1 = 0.f; st.m0 = s0.y; st.m1 = s1.y;
  }
  int aleft = 3; lens >>= 4; an++; bn++; acur += 4096;
#pragma unroll 1
  for (int s = 0; s < nst; s++) {
    uint32_t aa[SPS];
#pragma unroll
    for (int i = 0; i < SPS; i++) {
      if (aleft == 0) {
        acur = c.abase + (an & 3) * ASLOT;
        mbar_wait(c.fulla + (an & 3) * 8, (an >> 2) & 1);
        if (STATS) {
          float2 s0 = lds2f(acur + strow), s1 = lds2f(acur + strow + 64);
          float d0 = s0.x - st.c0, d1 = s1.x - st.c1;
          st.a0 += d0; st.a1 += d1;
          st.m0 += fmaf(80.f * d0, d0, s0.y); st.m1 += fmaf(80.f * d1, d1, s1.y);
        }
        aleft = (int)(lens & 15); lens >>= 4; an++;
      }
      aa[i] = acur; acur += 2048; aleft--;
    }
    const uint32_t bs = c.sb + (bn & (NBS - 1)) * BSLOT;
    mbar_wait(c.sb + BAR_FULLB + (bn & (NBS - 1)) * 8, (bn / NBS) & 1);
    if (N == 240) fence_async_smem();
    wg_fence();
#pragma unroll
    for (int i = 0; i < SPS; i++) wgmma_ss1(acc, DESC_A | enc(aa[i]), DESC_B | enc(bs + i * SLAB));
    wg_commit();
    wg_wait<1>();
    mbar_arrive_if(c.sb + BAR_EMPTYB + ((bn - 1) & (NBS - 1)) * 8, el);
    mbar_arrive_if(c.emptya + (arel & 3) * 8, el && arel < afin); if (arel < afin) arel++;
    if (SPS == 3) { mbar_arrive_if(c.emptya + (arel & 3) * 8, el && arel < afin); if (arel < afin) arel++; }
    afin = (aleft == 0) ? an : an - 1;
    bn++;
  }
  if (SPS == 3) {
    if (tail) {
      const uint32_t bs = c.sb + (bn & (NBS - 1)) * BSLOT;
      mbar_wait(c.sb + BAR_FULLB + (bn & (NBS - 1)) * 8, (bn / NBS) & 1);
      wg_fence();
      wgmma_ss1(acc, DESC_A | enc(acur), DESC_B | enc(bs));
      wg_commit();
      wg_wait<0>();
      mbar_arrive_if(c.sb + BAR_EMPTYB + ((bn - 1) & (NBS - 1)) * 8, el);
      bn++;
    }
  }
  wg_wait<0>();
  mbar_arrive_if(c.sb + BAR_EMPTYB + ((bn - 1) & (NBS - 1)) * 8, el);
  mbar_arrive_if(c.emptya + (arel & 3) * 8, el && arel < an); if (arel < an) arel++;
  mbar_arrive_if(c.emptya + (arel & 3) * 8, el && arel < an);
  c.an = an; c.bn = bn;
}

__device__ __forceinline__ void ln_coef(const Stats& st, float& rs0, float& nm0, float& rs1, float& nm1) {
  float mean0 = fmaf(st.a0, 0.125f, st.c0), mean1 = fmaf(st.a1, 0.125f, st.c1);
  float v0 = fmaxf(fmaf(-10.f * st.a0, st.a0, st.m0), 0.f) * (1.f / 640.f), v1 = fmaxf(fmaf(-10.f * st.a1, st.a1, st.m1), 0.f) * (1.f / 640.f);
  rs0 = rsqrtf(v0 + 1e-5f); rs1 = rsqrtf(v1 + 1e-5f);
  nm0 = -mean0 * rs0; nm1 = -mean1 * rs1;
}

__device__ __forceinline__ void slice_stats(const uint32_t (&xr)[20], uint32_t slot, int wi, int lane) {
  float s0 = 0.f, s1 = 0.f;
#pragma unroll
  for (int e = 0; e < 10; e++) { s0 += blo(xr[2 * e]) + bhi(xr[2 * e]); s1 += blo(xr[2 * e + 1]) + bhi(xr[2 * e + 1]); }
  s0 += __shfl_xor_sync(~0u, s0, 1); s1 += __shfl_xor_sync(~0u, s1, 1);
  s0 += __shfl_xor_sync(~0u, s0, 2); s1 += __shfl_xor_sync(~0u, s1, 2);
  s0 *= (1.f / 80.f); s1 *= (1.f / 80.f);
  float q0 = 0.f, q1 = 0.f;
#pragma unroll
  for (int e = 0; e < 10; e++) {
    float a = blo(xr[2 * e]) - s0, b = bhi(xr[2 * e]) - s0, cc = blo(xr[2 * e + 1]) - s1, d = bhi(xr[2 * e + 1]) - s1;
    q0 = fmaf(a, a, q0); q0 = fmaf(b, b, q0); q1 = fmaf(cc, cc, q1); q1 = fmaf(d, d, q1);
  }
  q0 += __shfl_xor_sync(~0u, q0, 1); q1 += __shfl_xor_sync(~0u, q1, 1);
  q0 += __shfl_xor_sync(~0u, q0, 2); q1 += __shfl_xor_sync(~0u, q1, 2);
  if ((lane & 3) == 0) {
    uint32_t a = slot + ADATA + (uint32_t)(wi * 16 + (lane >> 2)) * 8;
    sts2u(a, __float_as_uint(s0), __float_as_uint(q0));
    sts2u(a + 64, __float_as_uint(s1), __float_as_uint(q1));
  }
}

template <int R>
__device__ __forceinline__ void pair_reduce(const float (&acc)[80], uint32_t (&xr)[20], uint32_t l0, uint32_t l1, uint32_t fb0, uint32_t fb1,
                                            uint32_t par0, uint32_t par1, int t128) {
  const uint32_t r0 = mapa(l0 + t128 * 16, R ^ 1), r1 = mapa(l1 + t128 * 16, R ^ 1), rb0 = mapa(fb0, R ^ 1), rb1 = mapa(fb1, R ^ 1);
  constexpr int SO = R ? 0 : 40, KO = R ? 40 : 0;
#pragma unroll
  for (int i = 0; i < 10; i++)
    st_async4((i < 5 ? r0 : r1) + (i % 5) * 2048, acc[SO + 4 * i], acc[SO + 4 * i + 1], acc[SO + 4 * i + 2], acc[SO + 4 * i + 3], i < 5 ? rb0 : rb1);
  float k[40];
#pragma unroll
  for (int e = 0; e < 10; e++) {
    k[4 * e] = acc[KO + 4 * e] + blo(xr[2 * e]); k[4 * e + 1] = acc[KO + 4 * e + 1] + bhi(xr[2 * e]);
    k[4 * e + 2] = acc[KO + 4 * e + 2] + blo(xr[2 * e + 1]); k[4 * e + 3] = acc[KO + 4 * e + 3] + bhi(xr[2 * e + 1]);
  }
  mbar_wait_cl(fb0, par0);
#pragma unroll
  for (int e = 0; e < 5; e++) {
    float4 v = lds4f(l0 + t128 * 16 + e * 2048);
    xr[2 * e] = pack2(k[4 * e] + v.x, k[4 * e + 1] + v.y); xr[2 * e + 1] = pack2(k[4 * e + 2] + v.z, k[4 * e + 3] + v.w);
  }
  mbar_wait_cl(fb1, par1);
#pragma unroll
  for (int e = 5; e < 10; e++) {
    float4 v = lds4f(l1 + t128 * 16 + (e - 5) * 2048);
    xr[2 * e] = pack2(k[4 * e] + v.x, k[4 * e + 1] + v.y); xr[2 * e + 1] = pack2(k[4 * e + 2] + v.z, k[4 * e + 3] + v.w);
  }
}

__device__ __forceinline__ constexpr int blk(int part, int e) { return e < 8 ? 8 * part + e : 24 + 2 * part + (e - 8); }

__global__ void __cluster_dims__(2, 1, 1) __launch_bounds__(384, 1) mega_kernel(const __grid_constant__ Params P) {
  extern __shared__ __align__(1024) uint8_t smem_raw[];
  const uint32_t sb = (s2u(smem_raw) + 1023) & ~1023u;
  const int tid = threadIdx.x, lane = tid & 31;
  const int warp = __shfl_sync(~0u, tid >> 5, 0);
  const int m = blockIdx.x >> 3, j = blockIdx.x & 7;
  const uint32_t epoch = *(volatile uint32_t*)&gEpoch[blockIdx.x];
  const uint32_t tag = epoch + 1, fbase = epoch * 8;
  STAMP(warp < 8 ? (warp >> 2) : 2, 0);

  if (tid == 256) {
    for (int s = 0; s < (int)NBS; s++) { mbar_init(sb + BAR_FULLB + 8 * s, 1); mbar_init(sb + BAR_EMPTYB + 8 * s, 8); }
    for (int s = 0; s < 8; s++) { mbar_init(sb + BAR_FULLA + 8 * s, 1); mbar_init(sb + BAR_EMPTYA + 8 * s, 4); }
    for (int s = 0; s < 2; s++) { mbar_init(sb + BAR_LAND + 8 * s, 1); mbar_init(sb + BAR_PUSH + 8 * s, 1); }
    mbar_init(sb + BAR_CS, 8); mbar_init(sb + BAR_CS + 8, 1); mbar_init(sb + BAR_CS + 16, 1);
    asm volatile("fence.mbarrier_init.release.cluster;" ::: "memory");
    fence_async_smem();
  }
  __syncthreads();
  asm volatile("barrier.cluster.arrive.release.aligned;" ::: "memory");

  if (warp >= 8) {
    asm volatile("setmaxnreg.dec.sync.aligned.u32 40;");
    if (warp == 8) {
      uint32_t bn = 0;
      uint32_t rdst[3]; const __nv_bfloat16* rsrc[3];
#pragma unroll
      for (int i = 0; i < 3; i++) {
        const int q = lane + 32 * i, row = q / 6, cc = q % 6;
        rdst[i] = 6144 + row * 128 + ((cc ^ (row & 7)) << 4);
        rsrc[i] = P.wqkv + row * 1920 + (cc >> 1) * 640 + 80 * j + 64 + 8 * (cc & 1);
      }
#pragma unroll 1
      for (int p = 0; p < 2 * NHL; p++) {
        const int ty = p & 3;
        if (ty == 0) {
#pragma unroll 1
          for (int st = 0; st < 20; st++, bn++) {
            const uint32_t s = bn & (NBS - 1), dst = sb + s * BSLOT, fb = sb + BAR_FULLB + 8 * s;
            const int k0 = 80 * (j ^ ((2 * st) / 5)) + 16 * ((2 * st) % 5), k1 = 80 * (j ^ ((2 * st + 1) / 5)) + 16 * ((2 * st + 1) % 5);
            mbar_wait(sb + BAR_EMPTYB + 8 * s, ((bn / NBS) & 1) ^ 1);
            if (lane == 0) {
              asm volatile("mbarrier.expect_tx.shared::cta.b64 [%0], %1;" ::"r"(fb), "r"(12288) : "memory");
              tma3d(dst, &P.tq, 80 * j, k0, 0, fb);
              tma3d(dst + 8192, &P.tq, 80 * j, k1, 0, fb);
            }
#pragma unroll
            for (int i = 0; i < 3; i++) {
              asm volatile("cp.async.cg.shared.global [%0], [%1], 16;" ::"r"(dst + rdst[i]), "l"(rsrc[i] + k0 * 1920) : "memory");
              asm volatile("cp.async.cg.shared.global [%0], [%1], 16;" ::"r"(dst + 8192 + rdst[i]), "l"(rsrc[i] + k1 * 1920) : "memory");
            }
            asm volatile("cp.async.mbarrier.arrive.shared::cta.b64 [%0];" ::"r"(fb) : "memory");
            __syncwarp();
            if (lane == 0) mbar_arrive(fb);
          }
        } else {
          const int nch = ty == 1 ? 4 : ty == 3 ? 12 : 8;
          const int sps = (ty & 1) ? 3 : 2;
          const uint32_t slab = (ty & 1) ? 5120 : 8192, bytes = ty == 2 ? 7168 : 5120;
          const CUtensorMap* tm = ty == 1 ? &P.to : ty == 2 ? &P.t1 : &P.t2;
          const int c2 = ty == 2 ? (h_start(j) >> 5) : 5 * (j >> 1);
          int left = 0, pos = 0, rem = ty == 1 ? 20 : ty == 3 ? 54 : 40; bool first = true; uint32_t dst = 0, fb = 0;
#pragma unroll 1
          for (int ch = 0; ch < nch; ch++) {
            int k, len = 5;
            if (ty == 3) { int sl = j ^ (2 * (ch / 3)), t = ch % 3; k = h_start(sl) + 80 * t; if (t == 2) len = sl < 6 ? 4 : 2; }
            else k = 80 * (j ^ (ty == 1 ? 2 * ch : ch));
#pragma unroll 1
            for (int i = 0; i < len; i++, k += 16) {
              if (left == 0) {
                left = first ? 2 : min(sps, rem); rem -= left; first = false; pos = 0;
                const uint32_t s = bn & (NBS - 1);
                mbar_wait(sb + BAR_EMPTYB + 8 * s, ((bn / NBS) & 1) ^ 1);
                dst = sb + s * BSLOT; fb = sb + BAR_FULLB + 8 * s;
                if (lane == 0) mbar_expect(fb, bytes * left);
                bn++;
              }
              if (lane == 0) tma3d(dst + pos * slab, tm, 0, k, c2, fb);
              pos++; left--;
            }
          }
        }
      }
      asm volatile("cp.async.wait_all;" ::: "memory");
      asm volatile("barrier.cluster.wait.acquire.aligned;" ::: "memory");
    } else if (warp == 9) {
      asm volatile("barrier.cluster.wait.acquire.aligned;" ::: "memory");
      mbar_wait(sb + BAR_CS, 0);
      if (lane == 0) {
        l2_prefetch((const uint8_t*)P.wo + blockIdx.x * 6400, 6400);
        l2_prefetch((const uint8_t*)P.w1 + blockIdx.x * 17280, 17280);
        l2_prefetch((const uint8_t*)P.w2 + blockIdx.x * 17280, 17280);
      }
      if (lane < 16 && m < 15) {
        float s = 0.f;
#pragma unroll
        for (int w = 0; w < 8; w++) s += lds1f(sb + OFF_CSP + (w * 16 + lane) * 4);
        asm volatile("{.reg .b64 u; mov.b64 u, {%1,%2}; st.relaxed.gpu.global.b64 [%0], u;}" ::"l"(&gCS[j * 256 + m * 16 + lane]), "r"(__float_as_uint(s)), "r"(tag) : "memory");
      }
#pragma unroll 1
      for (int mat = 0; mat < 2; mat++) {
        const int ncol = mat == 0 ? 240 : (j < 6 ? 224 : 192);
        if (mat == 1 && m * 16 < ncol) {
          float v[8];
#pragma unroll
          for (int i = 0; i < 8; i++) v[i] = 0.f;
          const __nv_bfloat16* src = P.w1 + (size_t)(lane >> 1) * DFF_ + h_start(j) + m * 16 + (lane & 1) * 8;
#pragma unroll 1
          for (int it = 0; it < 10; it++) {
            uint4 u[4];
#pragma unroll
            for (int i = 0; i < 4; i++) u[i] = ldg_nc(src + (size_t)(it * 64 + i * 16) * DFF_);
#pragma unroll
            for (int i = 0; i < 4; i++) {
              v[0] += blo(u[i].x); v[1] += bhi(u[i].x); v[2] += blo(u[i].y); v[3] += bhi(u[i].y);
              v[4] += blo(u[i].z); v[5] += bhi(u[i].z); v[6] += blo(u[i].w); v[7] += bhi(u[i].w);
            }
          }
#pragma unroll
          for (int i = 0; i < 8; i++) {
#pragma unroll
            for (int o = 2; o < 32; o <<= 1) v[i] += __shfl_xor_sync(~0u, v[i], o);
          }
          if (lane < 2) {
#pragma unroll
            for (int i = 0; i < 4; i++) st_ll2(&gCS[(8 + j) * 256 + m * 16 + lane * 8 + 2 * i], __float_as_uint(v[2 * i]), __float_as_uint(v[2 * i + 1]), tag);
          }
        }
#pragma unroll 1
        for (int i = 0; i < 4; i++) {
          const int col = i * 64 + lane * 2;
          if (col < ncol) {
            uint4 v; uint32_t n = 0;
            while (true) { v = ld_ll2(&gCS[(mat * 8 + j) * 256 + col]); if (v.y == tag && v.w == tag) break; if (++n > SPIN_LIMIT) __trap(); __nanosleep(100); }
            sts2u(sb + (mat ? OFF_CS3 : OFF_CS1) + col * 4, v.x, v.z);
          } else if (col < 256) sts2u(sb + (mat ? OFF_CS3 : OFF_CS1) + col * 4, 0, 0);
        }
        __syncwarp();
        if (lane == 0) mbar_arrive(sb + BAR_CS + 8 + 8 * mat);
        STAMP(2, 40 + mat);
      }
    } else {
      asm volatile("barrier.cluster.wait.acquire.aligned;" ::: "memory");
      const int w = warp - 10, u = 2 * m + w;
      const uint32_t abase = sb + OFF_A + w * 4 * ASLOT, fulla = sb + BAR_FULLA + w * 32, emptya = sb + BAR_EMPTYA + w * 32;
      const uint32_t peer = (j & 1) ^ 1;
      uint32_t an = 0;
#pragma unroll 1
      for (int p = 0; p < 2 * NHL; p++) {
        const int ty = p & 3;
        const uint32_t target = fbase + p + 1;
        const int nown = ty == 3 ? 3 : 1, nch = ty == 1 ? 4 : ty == 3 ? 12 : 8;
        {
          const uint32_t e = an + nown - 1;
          if (e >= 4) mbar_wait(emptya + (e & 3) * 8, ((e - 4) >> 2) & 1);
          mbar_wait(fulla + (e & 3) * 8, (e >> 2) & 1);
        }
        STAMP(2 + w, 1 + 4 * p);
        if (lane == 0) {
          const uint32_t src = abase + (an & 3) * ASLOT;
          if (ty == 3) {
            uint8_t* g = gH + (size_t)u * (216 * 1024) + (h_start(j) >> 3) * 1024;
            bulk_s2g(g, src, ADATA);
            bulk_s2g(g + ADATA, abase + ((an + 1) & 3) * ASLOT, ADATA);
            bulk_s2g(g + 2 * ADATA, abase + ((an + 2) & 3) * ASLOT, j < 6 ? 8192 : 4096);
          } else if (ty == 1) {
            bulk_s2g(gO + (size_t)(u * 8 + j) * ADATA, src, ADATA);
          } else {
            bulk_s2g(gX + (size_t)(u * 8 + j) * ASLOT, src, ASLOT);
            const uint32_t s1 = (an + 1) & 3;
            bulk_s2s(mapa(abase + s1 * ASLOT, peer), src, ASLOT, mapa(fulla + s1 * 8, peer));
            mbar_expect(fulla + s1 * 8, ASLOT);
          }
          asm volatile("cp.async.bulk.commit_group;" ::: "memory");
          asm volatile("cp.async.bulk.wait_group 0;" ::: "memory");
          fence_async_glob();
          asm volatile("st.release.gpu.global.u32 [%0], %1;" ::"l"(&gFlag[u * 32 + j]), "r"(target) : "memory");
        }
        __syncwarp();
        STAMP(2 + w, 2 + 4 * p);
        uint32_t ready = 0;
        const int cfirst = (ty & 1) ? nown : 2;
#pragma unroll 1
        for (int ch = cfirst; ch < nch; ch++) {
          const uint32_t e = an + ch;
          int sl; const uint8_t* g; uint32_t bytes;
          if (ty == 3) { sl = j ^ (2 * (ch / 3)); int t = ch % 3; g = gH + (size_t)u * (216 * 1024) + ((h_start(sl) >> 3) + 10 * t) * 1024; bytes = t < 2 ? ADATA : (sl < 6 ? 8192 : 4096); }
          else if (ty == 1) { sl = j ^ (2 * ch); g = gO + (size_t)(u * 8 + sl) * ADATA; bytes = ADATA; }
          else { sl = j ^ ch; g = gX + (size_t)(u * 8 + sl) * ASLOT; bytes = ASLOT; }
          uint32_t n = 0;
          while (!((ready >> sl) & 1)) {
            uint32_t v = target;
            if (lane < 8) asm volatile("ld.acquire.gpu.global.u32 %0, [%1];" : "=r"(v) : "l"(&gFlag[u * 32 + lane]) : "memory");
            ready = __ballot_sync(~0u, (int)(v - target) >= 0);
            if (++n > SPIN_LIMIT) __trap();
          }
          if (!(ty & 1) && ch == 4) {
            const uint32_t e1 = an + 1;
            mbar_wait(fulla + (e1 & 3) * 8, (e1 >> 2) & 1);
            if (lane == 0) mbar_arrive_remote(mapa(sb + BAR_PUSH + 8 * w, peer));
            mbar_wait(sb + BAR_PUSH + 8 * w, (p >> 1) & 1);
          }
          if (e >= 4) mbar_wait(emptya + (e & 3) * 8, ((e - 4) >> 2) & 1);
          if (lane == 0) {
            if (n) fence_async_glob();
            mbar_expect(fulla + (e & 3) * 8, bytes);
            bulk_g2s(abase + (e & 3) * ASLOT, g, bytes, fulla + (e & 3) * 8);
          }
          __syncwarp();
          if (ch == cfirst) STAMP(2 + w, 3 + 4 * p);
        }
        STAMP(2 + w, 4 + 4 * p);
        an += nch;
        if (ty & 1) {
          mbar_wait(emptya + (an & 3) * 8, ((an - 4) >> 2) & 1);
          mbar_wait(emptya + ((an + 1) & 3) * 8, ((an - 3) >> 2) & 1);
          if (lane == 0) {
            mbar_expect(fulla + (an & 3) * 8, ADATA);
            mbar_expect(fulla + ((an + 1) & 3) * 8, ADATA);
            mbar_arrive_remote(mapa(sb + BAR_LAND + 8 * w, peer));
          }
          __syncwarp();
          an += 2;
        }
      }
    }
  } else {
    asm volatile("setmaxnreg.inc.sync.aligned.u32 232;");
    const int w = warp >> 2, wi = warp & 3, t128 = tid & 127, u = 2 * m + w;
    const int g = lane >> 2, t = lane & 3;
    Ctx c; c.sb = sb; c.abase = sb + OFF_A + w * 4 * ASLOT; c.fulla = sb + BAR_FULLA + w * 32; c.emptya = sb + BAR_EMPTYA + w * 32;
    c.an = 0; c.bn = 0; c.lane = lane; c.wi = wi;
    const uint32_t mtx = (uint32_t)((lane >> 4) * 1024 + (wi * 16 + (lane & 15)) * 16);
    uint32_t xr[20];
    {
      uint4 v[5], cw[5];
#pragma unroll
      for (int i = 0; i < 5; i++) {
        const int idx = (lane >> 3) + 4 * i, row = wi * 16 + (idx / 10) * 8 + (lane & 7);
        v[i] = ldg_nc(P.x + (size_t)(128 * m + 2 * row + w) * D_ + 80 * j + 8 * (idx % 10));
      }
      if (m < 15) {
        const int b = 2 * m + (lane & 1);
        const int col = b < 24 ? (b >> 3) * 640 + 80 * j + 8 * (b & 7) : ((b - 24) >> 1) * 640 + 80 * j + 64 + 8 * (b & 1);
#pragma unroll
        for (int i = 0; i < 5; i++) cw[i] = ldg_nc(P.wqkv + (size_t)((tid >> 1) + 128 * i) * 1920 + col);
      } else {
#pragma unroll
        for (int i = 0; i < 5; i++) cw[i] = make_uint4(0, 0, 0, 0);
      }
#pragma unroll
      for (int i = 0; i < 5; i++) {
        const int idx = (lane >> 3) + 4 * i, row = wi * 16 + (idx / 10) * 8 + (lane & 7);
        sts4u(c.abase + (idx % 10) * 1024 + row * 16, v[i]);
      }
      __syncwarp();
#pragma unroll
      for (int i = 0; i < 5; i++) ldsm4(c.abase + mtx + i * 2048, xr[4 * i], xr[4 * i + 1], xr[4 * i + 2], xr[4 * i + 3]);
      slice_stats(xr, c.abase, wi, lane);
      fence_async_smem();
      bar_sync(1 + w, 128);
      mbar_arrive_if(c.fulla, t128 == 0);
      float s[8];
#pragma unroll
      for (int i = 0; i < 8; i++) s[i] = 0.f;
#pragma unroll
      for (int i = 0; i < 5; i++) {
        s[0] += blo(cw[i].x); s[1] += bhi(cw[i].x); s[2] += blo(cw[i].y); s[3] += bhi(cw[i].y);
        s[4] += blo(cw[i].z); s[5] += bhi(cw[i].z); s[6] += blo(cw[i].w); s[7] += bhi(cw[i].w);
      }
#pragma unroll
      for (int i = 0; i < 4; i++) { bool hi = lane & 8; float snd = hi ? s[i] : s[i + 4], kp = hi ? s[i + 4] : s[i]; s[i] = kp + __shfl_xor_sync(~0u, snd, 8); }
#pragma unroll
      for (int i = 0; i < 2; i++) { bool hi = lane & 4; float snd = hi ? s[i] : s[i + 2], kp = hi ? s[i + 2] : s[i]; s[i] = kp + __shfl_xor_sync(~0u, snd, 4); }
      { bool hi = lane & 2; float snd = hi ? s[0] : s[1], kp = hi ? s[1] : s[0]; s[0] = kp + __shfl_xor_sync(~0u, snd, 2); }
      s[0] += __shfl_xor_sync(~0u, s[0], 16);
      if (lane < 16) sts1f(sb + OFF_CSP + (warp * 16 + (lane & 1) * 8 + (lane >> 1)) * 4, s[0]);
      __syncwarp();
      mbar_arrive_if(sb + BAR_CS, lane == 0);
    }
    asm volatile("barrier.cluster.wait.acquire.aligned;" ::: "memory");
    STAMP(w, 1);
    Stats st;
#pragma unroll 1
    for (int hl = 0; hl < NHL; hl++) {
      if (!(hl & 1)) {
        float acc[120];
        mainloop<240, 2, true>(acc, c, 19, false, 0x55555555ull, st);
        STAMP(w, 2 + 8 * hl);
        float rs0, nm0, rs1, nm1;
        ln_coef(st, rs0, nm0, rs1, nm1);
        if (hl == 0) mbar_wait(sb + BAR_CS + 8, 0);
        uint32_t Kl[10], Kh[10], Vl[10], Vh[10], Ql[10], Qh[10], Kp[10], Vp[10];
        const uint32_t csa = sb + OFF_CS1 + t * 8;
#pragma unroll
        for (int e = 0; e < 10; e++) {
          { const int b = blk(1, e); float2 cs = lds2f(csa + b * 32);
            Kl[e] = pack2(fmaf(acc[4 * b], rs0, cs.x * nm0), fmaf(acc[4 * b + 1], rs0, cs.y * nm0));
            Kh[e] = pack2(fmaf(acc[4 * b + 2], rs1, cs.x * nm1), fmaf(acc[4 * b + 3], rs1, cs.y * nm1)); }
          { const int b = blk(2, e); float2 cs = lds2f(csa + b * 32);
            Vl[e] = movm(pack2(fmaf(acc[4 * b], rs0, cs.x * nm0), fmaf(acc[4 * b + 1], rs0, cs.y * nm0)));
            Vh[e] = movm(pack2(fmaf(acc[4 * b + 2], rs1, cs.x * nm1), fmaf(acc[4 * b + 3], rs1, cs.y * nm1))); }
        }
        const uint32_t xb = c.abase + ((c.an + 1) & 3) * ASLOT + lane * 8;
        if (wi == 3) {
          if (m < 15) {
            uint4* hp = gHalo + (size_t)(((hl >> 1) * 32 + u) * 8 + j) * 320 + lane;
#pragma unroll
            for (int e = 0; e < 10; e++) st_ll2(hp + e * 32, Kh[e], Vh[e], tag);
          }
        } else {
#pragma unroll
          for (int e = 0; e < 10; e++) sts2u(xb + e * 1024 + wi * 256, Kh[e], Vh[e]);
        }
#pragma unroll
        for (int e = 0; e < 10; e++) {
          const int b = blk(0, e); float2 cs = lds2f(csa + b * 32);
          Ql[e] = pack2(fmaf(acc[4 * b], rs0, cs.x * nm0), fmaf(acc[4 * b + 1], rs0, cs.y * nm0));
          Qh[e] = pack2(fmaf(acc[4 * b + 2], rs1, cs.x * nm1), fmaf(acc[4 * b + 3], rs1, cs.y * nm1));
        }
        bar_sync(1 + w, 128);
        STAMP(w, 3 + 8 * hl);
        bool noprev = false;
        if (wi == 0) {
          if (m == 0) {
            noprev = true;
#pragma unroll
            for (int e = 0; e < 10; e++) Kp[e] = Vp[e] = 0;
          } else {
            const uint4* hp = gHalo + (size_t)(((hl >> 1) * 32 + u - 2) * 8 + j) * 320 + lane;
            uint32_t n = 0;
            while (true) {
              bool ok = true;
#pragma unroll
              for (int e = 0; e < 10; e++) { uint4 v = ld_ll2(hp + e * 32); Kp[e] = v.x; Vp[e] = v.z; ok = ok && v.y == tag && v.w == tag; }
              if (__all_sync(~0u, ok)) break;
              if (++n > SPIN_LIMIT) __trap();
            }
          }
        } else {
#pragma unroll
          for (int e = 0; e < 10; e++) { uint2 v = lds2u(xb + e * 1024 + (wi - 1) * 256); Kp[e] = v.x; Vp[e] = v.y; }
        }
        if (wi == 0) STAMP(w, 4 + 8 * hl);
        uint32_t o[20];
        constexpr float SC = 0.22360679774997896f * 1.4426950408889634f;
        const bool p0 = 2 * t > g, p1 = 2 * t + 1 > g;
#pragma unroll
        for (int hp = 0; hp < 2; hp++) {
          float osh[4];
#pragma unroll
          for (int od = 0; od < 2; od++) {
            const int e0 = 5 * hp + (od ? 3 : 0), e1 = e0 + 1, es = 5 * hp + 2;
            const bool mine = od ? (t >= 2) : (t < 2);
            const uint32_t qsl = mine ? Ql[es] : 0u, qsh = mine ? Qh[es] : 0u;
            float sa[4] = {0.f, 0.f, 0.f, 0.f}, sbb[4] = {0.f, 0.f, 0.f, 0.f}, sc[4] = {0.f, 0.f, 0.f, 0.f};
            mma16816(sa, Ql[e0], Qh[e0], Ql[e1], Qh[e1], Kp[e0], Kp[e1]); mma1688(sa, qsl, qsh, Kp[es]);
            mma16816(sbb, Ql[e0], Qh[e0], Ql[e1], Qh[e1], Kl[e0], Kl[e1]); mma1688(sbb, qsl, qsh, Kl[es]);
            mma16816(sc, Ql[e0], Qh[e0], Ql[e1], Qh[e1], Kh[e0], Kh[e1]); mma1688(sc, qsl, qsh, Kh[es]);
            float l0 = p0 ? sa[0] : sbb[0], l1 = p1 ? sa[1] : sbb[1], h0 = p0 ? sbb[2] : sc[2], h1 = p1 ? sbb[3] : sc[3];
            l0 *= SC; l1 *= SC; h0 *= SC; h1 *= SC;
            if (noprev) { if (p0) l0 = -1.4426950408889634e9f; if (p1) l1 = -1.4426950408889634e9f; }
            float ml = fmaxf(l0, l1), mh = fmaxf(h0, h1);
            ml = fmaxf(ml, __shfl_xor_sync(~0u, ml, 1)); mh = fmaxf(mh, __shfl_xor_sync(~0u, mh, 1));
            ml = fmaxf(ml, __shfl_xor_sync(~0u, ml, 2)); mh = fmaxf(mh, __shfl_xor_sync(~0u, mh, 2));
            l0 = ex2(l0 - ml); l1 = ex2(l1 - ml); h0 = ex2(h0 - mh); h1 = ex2(h1 - mh);
            float sl = l0 + l1, sh = h0 + h1;
            sl += __shfl_xor_sync(~0u, sl, 1); sh += __shfl_xor_sync(~0u, sh, 1);
            sl += __shfl_xor_sync(~0u, sl, 2); sh += __shfl_xor_sync(~0u, sh, 2);
            sl = __frcp_rn(sl); sh = __frcp_rn(sh);
            const uint32_t pl = pack2(l0 * sl, l1 * sl), ph = pack2(h0 * sh, h1 * sh);
            const uint32_t mk = (p0 ? 0xffffu : 0u) | (p1 ? 0xffff0000u : 0u);
            const uint32_t pa = pl & mk, pbl = pl & ~mk, pbh = ph & mk, pc = ph & ~mk;
#pragma unroll
            for (int z = 0; z < 3; z++) {
              const int e = z == 0 ? e0 : z == 1 ? e1 : es;
              float oc[4] = {0.f, 0.f, 0.f, 0.f};
              mma16816(oc, pa, 0u, pbl, pbh, Vp[e], Vl[e]); mma1688(oc, 0u, pc, Vh[e]);
              if (z < 2) { o[2 * e] = pack2(oc[0], oc[1]); o[2 * e + 1] = pack2(oc[2], oc[3]); }
              else if (od == 0) { osh[0] = oc[0]; osh[1] = oc[1]; osh[2] = oc[2]; osh[3] = oc[3]; }
              else { o[2 * e] = mine ? pack2(oc[0], oc[1]) : pack2(osh[0], osh[1]); o[2 * e + 1] = mine ? pack2(oc[2], oc[3]) : pack2(osh[2], osh[3]); }
            }
          }
        }
        const uint32_t slot = c.abase + (c.an & 3) * ASLOT;
#pragma unroll
        for (int i = 0; i < 5; i++) stsm4(slot + mtx + i * 2048, o[4 * i], o[4 * i + 1], o[4 * i + 2], o[4 * i + 3]);
        fence_async_smem();
        bar_sync(1 + w, 128);
        mbar_arrive_if(c.fulla + (c.an & 3) * 8, t128 == 0);
      } else {
        float acc[112];
        mainloop<224, 2, true>(acc, c, 19, false, 0x55555555ull, st);
        STAMP(w, 2 + 8 * hl);
        float rs0, nm0, rs1, nm1;
        ln_coef(st, rs0, nm0, rs1, nm1);
        if (hl == 1) mbar_wait(sb + BAR_CS + 16, 0);
        const uint32_t csa = sb + OFF_CS3 + t * 8;
#pragma unroll
        for (int i = 0; i < 14; i++) {
          uint32_t h[4];
#pragma unroll
          for (int z = 0; z < 2; z++) {
            const int b = 2 * i + z; float2 cs = lds2f(csa + b * 32);
            h[2 * z] = pack2_relu(fmaf(acc[4 * b], rs0, cs.x * nm0), fmaf(acc[4 * b + 1], rs0, cs.y * nm0));
            h[2 * z + 1] = pack2_relu(fmaf(acc[4 * b + 2], rs1, cs.x * nm1), fmaf(acc[4 * b + 3], rs1, cs.y * nm1));
          }
          stsm4(c.abase + ((c.an + i / 5) & 3) * ASLOT + mtx + (i % 5) * 2048, h[0], h[1], h[2], h[3]);
        }
        fence_async_smem();
        bar_sync(1 + w, 128);
        mbar_arrive_if(c.fulla + ((c.an + (uint32_t)t128) & 3) * 8, t128 < 3);
      }
      STAMP(w, 5 + 8 * hl);
      {
        float acc[80];
        mainloop<160, 3, false>(acc, c, (hl & 1) ? 17 : 6, hl & 1, (hl & 1) ? lens_w2(j) : 0x5555ull, st);
        STAMP(w, 6 + 8 * hl);
        const uint32_t e0 = c.an, e1 = c.an + 1;
        const uint32_t l0 = c.abase + (e0 & 3) * ASLOT, l1 = c.abase + (e1 & 3) * ASLOT, fb0 = c.fulla + (e0 & 3) * 8, fb1 = c.fulla + (e1 & 3) * 8;
        mbar_wait_cl(sb + BAR_LAND + 8 * w, hl & 1);
        if (j & 1) pair_reduce<1>(acc, xr, l0, l1, fb0, fb1, (e0 >> 2) & 1, (e1 >> 2) & 1, t128);
        else pair_reduce<0>(acc, xr, l0, l1, fb0, fb1, (e0 >> 2) & 1, (e1 >> 2) & 1, t128);
        STAMP(w, 7 + 8 * hl);
        __syncwarp();
        mbar_arrive_if(c.emptya + ((e0 + (uint32_t)lane) & 3) * 8, lane < 2);
        c.an += 2;
        const uint32_t slot = c.abase + (c.an & 3) * ASLOT;
#pragma unroll
        for (int i = 0; i < 5; i++) stsm4(slot + mtx + i * 2048, xr[4 * i], xr[4 * i + 1], xr[4 * i + 2], xr[4 * i + 3]);
        if (hl < NHL - 1) {
          slice_stats(xr, slot, wi, lane);
          fence_async_smem();
          bar_sync(1 + w, 128);
          mbar_arrive_if(c.fulla + (c.an & 3) * 8, t128 == 0);
        } else {
          __syncwarp();
#pragma unroll
          for (int i = 0; i < 5; i++) {
            const int idx = (lane >> 3) + 4 * i, row = wi * 16 + (idx / 10) * 8 + (lane & 7);
            uint4 v = lds4u(slot + (idx % 10) * 1024 + row * 16);
            *(uint4*)(P.out + (size_t)(128 * m + 2 * row + w) * D_ + 80 * j + 8 * (idx % 10)) = v;
          }
        }
        STAMP(w, 8 + 8 * hl);
      }
    }
    if (tid == 0) gEpoch[blockIdx.x] = epoch + 1;
  }
}

typedef CUresult (*EncFn)(CUtensorMap*, CUtensorMapDataType, cuuint32_t, void*, const cuuint64_t*, const cuuint64_t*, const cuuint32_t*,
                          const cuuint32_t*, CUtensorMapInterleave, CUtensorMapSwizzle, CUtensorMapL2promotion, CUtensorMapFloatOOBfill);

void make3d(EncFn enc, CUtensorMap* mp, const void* p, uint64_t d0, uint64_t d1, uint64_t d2, uint64_t s1, uint64_t s2, uint32_t b0, uint32_t b1,
            uint32_t b2, CUtensorMapSwizzle sw) {
  cuuint64_t d[3] = {d0, d1, d2}, s[2] = {s1, s2};
  cuuint32_t b[3] = {b0, b1, b2}, e[3] = {1, 1, 1};
  enc(mp, CU_TENSOR_MAP_DATA_TYPE_BFLOAT16, 3, (void*)p, d, s, b, e, CU_TENSOR_MAP_INTERLEAVE_NONE, sw, CU_TENSOR_MAP_L2_PROMOTION_L2_128B,
      CU_TENSOR_MAP_FLOAT_OOB_FILL_NONE);
}

}

extern "C" void kernel_launch(void* const* d_in, const int* in_sizes, int n_in, void* d_out, int out_size) {
  (void)in_sizes; (void)n_in; (void)out_size;
  static EncFn enc = nullptr;
  if (!enc) {
    void* f = nullptr; cudaDriverEntryPointQueryResult q;
    cudaGetDriverEntryPoint("cuTensorMapEncodeTiled", &f, cudaEnableDefault, &q);
    enc = (EncFn)f;
    cudaFuncSetAttribute(mega_kernel, cudaFuncAttributeMaxDynamicSharedMemorySize, SMEM_BYTES);
  }
  Params P;
  P.x = (const __nv_bfloat16*)d_in[0]; P.wqkv = (const __nv_bfloat16*)d_in[1]; P.wo = (const __nv_bfloat16*)d_in[2];
  P.w1 = (const __nv_bfloat16*)d_in[4]; P.w2 = (const __nv_bfloat16*)d_in[5]; P.out = (__nv_bfloat16*)d_out;
  make3d(enc, &P.tq, P.wqkv, 640, 640, 3, 3840, 1280, 64, 16, 3, CU_TENSOR_MAP_SWIZZLE_128B);
  make3d(enc, &P.to, P.wo, 32, 640, 20, 1280, 64, 32, 16, 5, CU_TENSOR_MAP_SWIZZLE_64B);
  make3d(enc, &P.t1, P.w1, 32, 640, 54, 3456, 64, 32, 16, 7, CU_TENSOR_MAP_SWIZZLE_64B);
  make3d(enc, &P.t2, P.w2, 32, 1728, 20, 1280, 64, 32, 16, 5, CU_TENSOR_MAP_SWIZZLE_64B);
  mega_kernel<<<NCTA, 384, SMEM_BYTES>>>(P);
}
```

```cpp
#include <cuda_runtime.h>
#include <cuda.h>
#include <cuda_bf16.h>
#include <stdint.h>

namespace {

constexpr int D_ = 640;
constexpr int NCTA = 128;
#define INFL 3
#define INFL_X 2
#define FIRST 3
#define GX 6
#define GH 8
#define IX 2
#define IO 3
#define IH 4
#define T1 5
#define T2 30
#define T3 38
#define XRAT 5
#define PVAT 10
#define LEADS 0x0303
#define SUMAT 8
#define SIDE 8
#define PF1 12
#define SWP 15
#define PS 3
constexpr int HPROBE = 7;
constexpr uint32_t SB0 = 1024;
constexpr uint32_t BSLOT = 15360, NBS = 11, NBB = 65;
constexpr uint32_t OFF_LAND = BSLOT * NBS;
constexpr uint32_t OFF_XCH = OFF_LAND + 20480;
constexpr uint32_t OFF_CSB = OFF_XCH;
constexpr uint32_t OFF_CS = OFF_CSB + 20480;
constexpr uint32_t OFF_TB = OFF_CS + 2048;
constexpr uint32_t BAR_FULLB = OFF_TB + 65 * 16, BAR_EMPTYB = BAR_FULLB + 8 * NBB;
constexpr uint32_t BAR_X = BAR_EMPTYB + 8 * NBB, BAR_X2 = BAR_X + 16, BAR_CS = BAR_X2 + 16, BAR_STRIP = BAR_CS + 16, BAR_LEAD = BAR_STRIP + 8;
constexpr uint32_t BAR_CSP = BAR_LEAD + 32, BAR_DONE = BAR_CSP + 8, OFF_CSP = BAR_DONE + 8, OFF_PROF = OFF_CSP + 1024;
constexpr uint32_t SMEM_BYTES = OFF_PROF;
static_assert(SMEM_BYTES <= 232448, "smem layout");

struct Scratch {
  uint4 x[32 * 40 * 128];
  uint4 o[32 * 40 * 128];
  uint4 h[32 * 108 * 128];
  uint4 part[32 * 8 * 5 * 128];
  float2 st[32 * 64 * 8];
  uint4 halo[2 * 32 * 8 * 5 * 32];
  uint2 cs[2 * 2 * 2048];
  uint32_t epoch[NCTA];
};
__device__ __align__(1024) Scratch gS;
extern __shared__ __align__(1024) uint8_t smem_raw[];
#define STAMP(role, i) do {} while (0)
#define GSTAMP(i) do {} while (0)

struct Ptrs {
  const __nv_bfloat16 *x, *wqkv;
  Scratch* s;
  __nv_bfloat16* out;
  const __nv_bfloat16 *w1, *w2;
};
struct Maps {
  CUtensorMap tx, tw[12], tc[2], to;
  const __nv_bfloat16* wo;
};

__device__ __forceinline__ uint32_t s2u(const void* p) { return (uint32_t)__cvta_generic_to_shared(p); }
__device__ __forceinline__ void mbar_init(uint32_t b, uint32_t c) { asm volatile("mbarrier.init.shared::cta.b64 [%0], %1;" ::"r"(b), "r"(c) : "memory"); }
__device__ __forceinline__ void mbar_expect(uint32_t b, uint32_t tx) { asm volatile("mbarrier.arrive.expect_tx.shared::cta.b64 _, [%0], %1;" ::"r"(b), "r"(tx) : "memory"); }
__device__ __forceinline__ void mbar_arrive(uint32_t b) { asm volatile("mbarrier.arrive.shared::cta.b64 _, [%0];" ::"r"(b) : "memory"); }
__device__ __forceinline__ void mbar_arrive_if(uint32_t b, bool p) {
  asm volatile("{.reg .pred p; setp.ne.u32 p, %1, 0; @p mbarrier.arrive.shared::cta.b64 _, [%0];}" ::"r"(b), "r"((uint32_t)p) : "memory"); }
__device__ __forceinline__ uint32_t mapa(uint32_t a, uint32_t cta) { uint32_t r; asm("mapa.shared::cluster.u32 %0, %1, %2;" : "=r"(r) : "r"(a), "r"(cta)); return r; }
__device__ __forceinline__ void mbar_wait(uint32_t b, uint32_t par) {
  asm volatile("{.reg .pred p;\nW: mbarrier.try_wait.parity.shared::cta.b64 p, [%0], %1;\n@!p bra W;\n}" ::"r"(b), "r"(par) : "memory"); }
__device__ __forceinline__ void mbar_wait_bounded(uint32_t b, uint32_t par) {
  asm volatile("{.reg .pred p; .reg .u64 t0, t1; mov.u64 t0, %%clock64;\n"
               "W: mbarrier.try_wait.parity.shared::cta.b64 p, [%0], %1;\n"
               "@p bra D;\n mov.u64 t1, %%clock64; sub.u64 t1, t1, t0; setp.lt.u64 p, t1, 2000000000; @p bra W; trap;\n D: }" ::"r"(b), "r"(par) : "memory"); }
__device__ __forceinline__ uint32_t mbar_peek(uint32_t b, uint32_t par) {
  uint32_t ok;
  asm volatile("{.reg .pred p; mbarrier.test_wait.parity.shared::cta.b64 p, [%1], %2; selp.u32 %0, 1, 0, p;}" : "=r"(ok) : "r"(b), "r"(par) : "memory");
  return ok; }
__device__ __forceinline__ void mbar_wait_unless(uint32_t ok, uint32_t b, uint32_t par) {
  asm volatile("{.reg .pred p; setp.ne.u32 p, %2, 0; @p bra D;\n"
               "W: mbarrier.try_wait.parity.shared::cta.b64 p, [%0], %1;\n@!p bra W;\n D: }" ::"r"(b), "r"(par), "r"(ok) : "memory"); }
__device__ __forceinline__ void tma2d(uint32_t dst, const CUtensorMap* m, int c0, int c1, uint32_t bar) {
  asm volatile("cp.async.bulk.tensor.2d.shared::cluster.global.mbarrier::complete_tx::bytes [%0], [%1, {%3,%4}], [%2];"
               ::"r"(dst), "l"(m), "r"(bar), "r"(c0), "r"(c1) : "memory"); }
__device__ __forceinline__ void tma3d(uint32_t dst, const CUtensorMap* m, int c0, int c1, int c2, uint32_t bar) {
  asm volatile("cp.async.bulk.tensor.3d.shared::cluster.global.mbarrier::complete_tx::bytes [%0], [%1, {%3,%4,%5}], [%2];"
               ::"r"(dst), "l"(m), "r"(bar), "r"(c0), "r"(c1), "r"(c2) : "memory"); }
__device__ __forceinline__ void tma4d(uint32_t dst, const void* m, int c0, int c2, int c3, uint32_t bar) {
  asm volatile("cp.async.bulk.tensor.4d.shared::cluster.global.mbarrier::complete_tx::bytes [%0], [%1, {%3,%4,%5,%6}], [%2];"
               ::"r"(dst), "l"(m), "r"(bar), "r"(c0), "r"(0), "r"(c2), "r"(c3) : "memory"); }
__device__ __forceinline__ void tma4d_mc(uint32_t dst, const void* m, int c0, int c2, int c3, uint32_t bar) {
  asm volatile("cp.async.bulk.tensor.4d.shared::cluster.global.mbarrier::complete_tx::bytes.multicast::cluster [%0], [%1, {%3,%4,%5,%6}], [%2], %7;"
               ::"r"(dst), "l"(m), "r"(bar), "r"(c0), "r"(0), "r"(c2), "r"(c3), "h"((uint16_t)3) : "memory"); }
__device__ __forceinline__ void mbar_arrive_cl_if(uint32_t b, bool p) {
  asm volatile("{.reg .pred p; setp.ne.u32 p, %1, 0; @p mbarrier.arrive.shared::cluster.b64 _, [%0];}" ::"r"(b), "r"((uint32_t)p) : "memory"); }
__device__ __forceinline__ void cluster_arrive() { asm volatile("barrier.cluster.arrive.relaxed.aligned;" ::: "memory"); }
__device__ __forceinline__ void cluster_wait() { asm volatile("barrier.cluster.wait.aligned;" ::: "memory"); }
__device__ __forceinline__ void l2_prefetch(const void* p, uint32_t bytes) { asm volatile("cp.async.bulk.prefetch.L2.global [%0], %1;" ::"l"(p), "r"(bytes) : "memory"); }
__device__ __forceinline__ void bar_sync(int id, int n) { asm volatile("bar.sync %0, %1;" ::"r"(id), "r"(n) : "memory"); }
__device__ __forceinline__ void wg_fence() { asm volatile("wgmma.fence.sync.aligned;" ::: "memory"); }
__device__ __forceinline__ void wg_commit() { asm volatile("wgmma.commit_group.sync.aligned;" ::: "memory"); }
template <int N> __device__ __forceinline__ void wg_wait() { asm volatile("wgmma.wait_group.sync.aligned %0;" ::"n"(N) : "memory"); }
__device__ __forceinline__ bool elect() {
  uint32_t p; asm volatile("{.reg .pred p; elect.sync _|p, 0xffffffff; selp.u32 %0, 1, 0, p;}" : "=r"(p)); return p; }
__device__ __forceinline__ void stsm4(uint32_t a, const uint4& r) {
  asm volatile("stmatrix.sync.aligned.m8n8.x4.shared.b16 [%0], {%1,%2,%3,%4};" ::"r"(a), "r"(r.x), "r"(r.y), "r"(r.z), "r"(r.w) : "memory"); }
__device__ __forceinline__ void ldsm4(uint32_t a, uint4& r) {
  asm volatile("ldmatrix.sync.aligned.m8n8.x4.shared.b16 {%0,%1,%2,%3}, [%4];" : "=r"(r.x), "=r"(r.y), "=r"(r.z), "=r"(r.w) : "r"(a) : "memory"); }
__device__ __forceinline__ uint32_t movm(uint32_t a) { uint32_t d; asm volatile("movmatrix.sync.aligned.m8n8.trans.b16 %0, %1;" : "=r"(d) : "r"(a)); return d; }
__device__ __forceinline__ uint32_t pack2(float lo, float hi) { uint32_t r; asm("cvt.rn.bf16x2.f32 %0, %1, %2;" : "=r"(r) : "f"(hi), "f"(lo)); return r; }
__device__ __forceinline__ uint32_t pack2_relu(float lo, float hi) { uint32_t r; asm("cvt.rn.relu.bf16x2.f32 %0, %1, %2;" : "=r"(r) : "f"(hi), "f"(lo)); return r; }
__device__ __forceinline__ float blo(uint32_t v) { return __uint_as_float(v << 16); }
__device__ __forceinline__ float bhi(uint32_t v) { return __uint_as_float(v & 0xffff0000u); }
__device__ __forceinline__ uint4 lds4u(uint32_t a) { uint4 v; asm volatile("ld.shared.v4.u32 {%0,%1,%2,%3}, [%4];" : "=r"(v.x), "=r"(v.y), "=r"(v.z), "=r"(v.w) : "r"(a) : "memory"); return v; }
__device__ __forceinline__ void sts4u(uint32_t a, const uint4& v) { asm volatile("st.shared.v4.u32 [%0], {%1,%2,%3,%4};" ::"r"(a), "r"(v.x), "r"(v.y), "r"(v.z), "r"(v.w) : "memory"); }
__device__ __forceinline__ void sts2u(uint32_t a, uint32_t x, uint32_t y) { asm volatile("st.shared.v2.u32 [%0], {%1,%2};" ::"r"(a), "r"(x), "r"(y) : "memory"); }
__device__ __forceinline__ void sts1u(uint32_t a, uint32_t x) { asm volatile("st.shared.u32 [%0], %1;" ::"r"(a), "r"(x) : "memory"); }
__device__ __forceinline__ uint4 ldg_nc(const void* p) { uint4 v; asm volatile("ld.global.nc.L1::no_allocate.v4.u32 {%0,%1,%2,%3}, [%4];" : "=r"(v.x), "=r"(v.y), "=r"(v.z), "=r"(v.w) : "l"(p) : "memory"); return v; }
__device__ __forceinline__ uint4 ldg_strong(const void* p) {
  uint4 v; asm volatile("ld.relaxed.gpu.global.v4.u32 {%0,%1,%2,%3}, [%4];" : "=r"(v.x), "=r"(v.y), "=r"(v.z), "=r"(v.w) : "l"(p) : "memory"); return v; }
__device__ __forceinline__ uint4 ld_strong(const void* p) {
  uint4 v; asm volatile("ld.relaxed.gpu.v4.u32 {%0,%1,%2,%3}, [%4];" : "=r"(v.x), "=r"(v.y), "=r"(v.z), "=r"(v.w) : "l"(p) : "memory"); return v; }
__device__ __forceinline__ void st_strong(void* p, const uint4& v) {
  asm volatile("st.relaxed.gpu.v4.u32 [%0], {%1,%2,%3,%4};" ::"l"(p), "r"(v.x), "r"(v.y), "r"(v.z), "r"(v.w) : "memory"); }
template <class T> __device__ __forceinline__ T* opaque(T* p) { asm volatile("" : "+l"(p)); return p; }
template <class T> __device__ __forceinline__ T* pinned(T* p) {
  asm volatile("{.reg .pred q; .reg .s32 h; mov.u32 h, %%clock_hi; setp.lt.s32 q, h, 0; @q st.global.u8 [%0], h;}" : "+l"(p) :: "memory");
  return p; }
template <int N> __device__ __forceinline__ bool stale(const uint4* v, uint32_t tz, uint32_t mask) {
  uint32_t b0, b1;
  asm("lop3.b32 %0, %1, %2, %3, 0x7e;" : "=r"(b0) : "r"(v[0].x), "r"(v[N - 1].x), "r"(tz));
  asm("lop3.b32 %0, %1, %2, %3, 0x7e;" : "=r"(b1) : "r"(v[1].x), "r"(v[2].x), "r"(tz));
#pragma unroll
  for (int z = 3; z < N - 1; z++) {
    if (z & 1) asm("lop3.b32 %0, %0, %1, %2, 0xf6;" : "+r"(b1) : "r"(v[z].x), "r"(tz));
    else asm("lop3.b32 %0, %0, %1, %2, 0xf6;" : "+r"(b0) : "r"(v[z].x), "r"(tz));
  }
  uint32_t r;
  asm volatile("{.reg .pred p, q; .reg .b32 d; setp.eq.u32 q, 0, 0; lop3.and.b32 d|p, %1, %2, %3, 0xa8, q; vote.sync.any.pred p, p, 0xffffffff; selp.u32 %0, 1, 0, p;}"
               : "=r"(r) : "r"(b0), "r"(b1), "r"(mask));
  return r;
}
__device__ __forceinline__ void shift_rows(uint4& v, uint32_t c0, uint32_t c1) {
  asm("sub.rn.bf16x2 %0, %0, %1;" : "+r"(v.x) : "r"(c0)); asm("sub.rn.bf16x2 %0, %0, %1;" : "+r"(v.y) : "r"(c1));
  asm("sub.rn.bf16x2 %0, %0, %1;" : "+r"(v.z) : "r"(c0)); asm("sub.rn.bf16x2 %0, %0, %1;" : "+r"(v.w) : "r"(c1)); }
__device__ __forceinline__ uint32_t tagged(uint32_t w, uint32_t tag) { return (w & ~1u) | tag; }
__device__ __forceinline__ void stg_strong(void* p, const uint4& v) {
  asm volatile("st.relaxed.gpu.global.v4.u32 [%0], {%1,%2,%3,%4};" ::"l"(p), "r"(v.x), "r"(v.y), "r"(v.z), "r"(v.w) : "memory"); }
__device__ __forceinline__ void stg_strong_if(void* p, const uint4& v, uint32_t pred) {
  asm volatile("{.reg .pred q; setp.ne.u32 q, %5, 0; @q st.relaxed.gpu.global.v4.u32 [%0], {%1,%2,%3,%4};}" ::"l"(p), "r"(v.x), "r"(v.y), "r"(v.z), "r"(v.w), "r"(pred) : "memory"); }
__device__ __forceinline__ void mma16816(float (&c)[4], uint32_t a0, uint32_t a1, uint32_t a2, uint32_t a3, uint32_t b0, uint32_t b1) {
  asm("mma.sync.aligned.m16n8k16.row.col.f32.bf16.bf16.f32 {%0,%1,%2,%3}, {%4,%5,%6,%7}, {%8,%9}, {%0,%1,%2,%3};"
      : "+f"(c[0]), "+f"(c[1]), "+f"(c[2]), "+f"(c[3]) : "r"(a0), "r"(a1), "r"(a2), "r"(a3), "r"(b0), "r"(b1)); }
__device__ __forceinline__ void mma1688(float (&c)[4], uint32_t a0, uint32_t a1, uint32_t b0) {
  asm("mma.sync.aligned.m16n8k8.row.col.f32.bf16.bf16.f32 {%0,%1,%2,%3}, {%4,%5}, {%6}, {%0,%1,%2,%3};"
      : "+f"(c[0]), "+f"(c[1]), "+f"(c[2]), "+f"(c[3]) : "r"(a0), "r"(a1), "r"(b0)); }
__device__ __forceinline__ float rcp(float x) { float r; asm("rcp.approx.ftz.f32 %0, %1;" : "=f"(r) : "f"(x)); return r; }
__device__ __forceinline__ float rsq(float x) { float r; asm("rsqrt.approx.ftz.f32 %0, %1;" : "=f"(r) : "f"(x)); return r; }
__device__ __forceinline__ float ex2(float x) { float r; asm("ex2.approx.ftz.f32 %0, %1;" : "=f"(r) : "f"(x)); return r; }

template <bool ZERO, uint64_t DESC> __device__ __forceinline__ void wgmma192(float* d, const uint4& a, uint32_t off) {
  if constexpr (ZERO)
    asm volatile("{.reg .b32 l; .reg .b64 q; add.u32 l, %100, %101; mov.b64 q, {l, %102};\n"
    "wgmma.mma_async.sync.aligned.m64n192k16.f32.bf16.bf16 {%0,%1,%2,%3,%4,%5,%6,%7,%8,%9,%10,%11,%12,%13,%14,%15,%16,%17,%18,%19,%20,%21,%22,%23,%24,%25,%26,%27,%28,%29,%30,%31,%32,%33,%34,%35,%36,%37,%38,%39,%40,%41,%42,%43,%44,%45,%46,%47,%48,%49,%50,%51,%52,%53,%54,%55,%56,%57,%58,%59,%60,%61,%62,%63,%64,%65,%66,%67,%68,%69,%70,%71,%72,%73,%74,%75,%76,%77,%78,%79,%80,%81,%82,%83,%84,%85,%86,%87,%88,%89,%90,%91,%92,%93,%94,%95}, {%96,%97,%98,%99}, q, 0, 1, 1, 1;}"
    : "=f"(d[0]),"=f"(d[1]),"=f"(d[2]),"=f"(d[3]),"=f"(d[4]),"=f"(d[5]),"=f"(d[6]),"=f"(d[7]),"=f"(d[8]),"=f"(d[9]),"=f"(d[10]),"=f"(d[11]),"=f"(d[12]),"=f"(d[13]),"=f"(d[14]),"=f"(d[15]),"=f"(d[16]),"=f"(d[17]),"=f"(d[18]),"=f"(d[19]),"=f"(d[20]),"=f"(d[21]),"=f"(d[22]),"=f"(d[23]),"=f"(d[24]),"=f"(d[25]),"=f"(d[26]),"=f"(d[27]),"=f"(d[28]),"=f"(d[29]),"=f"(d[30]),"=f"(d[31]),"=f"(d[32]),"=f"(d[33]),"=f"(d[34]),"=f"(d[35]),"=f"(d[36]),"=f"(d[37]),"=f"(d[38]),"=f"(d[39]),"=f"(d[40]),"=f"(d[41]),"=f"(d[42]),"=f"(d[43]),"=f"(d[44]),"=f"(d[45]),"=f"(d[46]),"=f"(d[47]),"=f"(d[48]),"=f"(d[49]),"=f"(d[50]),"=f"(d[51]),"=f"(d[52]),"=f"(d[53]),"=f"(d[54]),"=f"(d[55]),"=f"(d[56]),"=f"(d[57]),"=f"(d[58]),"=f"(d[59]),"=f"(d[60]),"=f"(d[61]),"=f"(d[62]),"=f"(d[63]),"=f"(d[64]),"=f"(d[65]),"=f"(d[66]),"=f"(d[67]),"=f"(d[68]),"=f"(d[69]),"=f"(d[70]),"=f"(d[71]),"=f"(d[72]),"=f"(d[73]),"=f"(d[74]),"=f"(d[75]),"=f"(d[76]),"=f"(d[77]),"=f"(d[78]),"=f"(d[79]),"=f"(d[80]),"=f"(d[81]),"=f"(d[82]),"=f"(d[83]),"=f"(d[84]),"=f"(d[85]),"=f"(d[86]),"=f"(d[87]),"=f"(d[88]),"=f"(d[89]),"=f"(d[90]),"=f"(d[91]),"=f"(d[92]),"=f"(d[93]),"=f"(d[94]),"=f"(d[95])
    : "r"(a.x), "r"(a.y), "r"(a.z), "r"(a.w), "r"(off), "n"((uint32_t)DESC), "n"((uint32_t)(DESC >> 32)));
  if constexpr (!ZERO)
    asm volatile("{.reg .b32 l; .reg .b64 q; add.u32 l, %100, %101; mov.b64 q, {l, %102};\n"
    "wgmma.mma_async.sync.aligned.m64n192k16.f32.bf16.bf16 {%0,%1,%2,%3,%4,%5,%6,%7,%8,%9,%10,%11,%12,%13,%14,%15,%16,%17,%18,%19,%20,%21,%22,%23,%24,%25,%26,%27,%28,%29,%30,%31,%32,%33,%34,%35,%36,%37,%38,%39,%40,%41,%42,%43,%44,%45,%46,%47,%48,%49,%50,%51,%52,%53,%54,%55,%56,%57,%58,%59,%60,%61,%62,%63,%64,%65,%66,%67,%68,%69,%70,%71,%72,%73,%74,%75,%76,%77,%78,%79,%80,%81,%82,%83,%84,%85,%86,%87,%88,%89,%90,%91,%92,%93,%94,%95}, {%96,%97,%98,%99}, q, 1, 1, 1, 1;}"
    : "+f"(d[0]),"+f"(d[1]),"+f"(d[2]),"+f"(d[3]),"+f"(d[4]),"+f"(d[5]),"+f"(d[6]),"+f"(d[7]),"+f"(d[8]),"+f"(d[9]),"+f"(d[10]),"+f"(d[11]),"+f"(d[12]),"+f"(d[13]),"+f"(d[14]),"+f"(d[15]),"+f"(d[16]),"+f"(d[17]),"+f"(d[18]),"+f"(d[19]),"+f"(d[20]),"+f"(d[21]),"+f"(d[22]),"+f"(d[23]),"+f"(d[24]),"+f"(d[25]),"+f"(d[26]),"+f"(d[27]),"+f"(d[28]),"+f"(d[29]),"+f"(d[30]),"+f"(d[31]),"+f"(d[32]),"+f"(d[33]),"+f"(d[34]),"+f"(d[35]),"+f"(d[36]),"+f"(d[37]),"+f"(d[38]),"+f"(d[39]),"+f"(d[40]),"+f"(d[41]),"+f"(d[42]),"+f"(d[43]),"+f"(d[44]),"+f"(d[45]),"+f"(d[46]),"+f"(d[47]),"+f"(d[48]),"+f"(d[49]),"+f"(d[50]),"+f"(d[51]),"+f"(d[52]),"+f"(d[53]),"+f"(d[54]),"+f"(d[55]),"+f"(d[56]),"+f"(d[57]),"+f"(d[58]),"+f"(d[59]),"+f"(d[60]),"+f"(d[61]),"+f"(d[62]),"+f"(d[63]),"+f"(d[64]),"+f"(d[65]),"+f"(d[66]),"+f"(d[67]),"+f"(d[68]),"+f"(d[69]),"+f"(d[70]),"+f"(d[71]),"+f"(d[72]),"+f"(d[73]),"+f"(d[74]),"+f"(d[75]),"+f"(d[76]),"+f"(d[77]),"+f"(d[78]),"+f"(d[79]),"+f"(d[80]),"+f"(d[81]),"+f"(d[82]),"+f"(d[83]),"+f"(d[84]),"+f"(d[85]),"+f"(d[86]),"+f"(d[87]),"+f"(d[88]),"+f"(d[89]),"+f"(d[90]),"+f"(d[91]),"+f"(d[92]),"+f"(d[93]),"+f"(d[94]),"+f"(d[95])
    : "r"(a.x), "r"(a.y), "r"(a.z), "r"(a.w), "r"(off), "n"((uint32_t)DESC), "n"((uint32_t)(DESC >> 32)));
}

template <bool ZERO, uint64_t DESC> __device__ __forceinline__ void wgmma128(float* d, const uint4& a, uint32_t off) {
  if constexpr (ZERO)
    asm volatile("{.reg .b32 l; .reg .b64 q; add.u32 l, %68, %69; mov.b64 q, {l, %70};\n"
    "wgmma.mma_async.sync.aligned.m64n128k16.f32.bf16.bf16 {%0,%1,%2,%3,%4,%5,%6,%7,%8,%9,%10,%11,%12,%13,%14,%15,%16,%17,%18,%19,%20,%21,%22,%23,%24,%25,%26,%27,%28,%29,%30,%31,%32,%33,%34,%35,%36,%37,%38,%39,%40,%41,%42,%43,%44,%45,%46,%47,%48,%49,%50,%51,%52,%53,%54,%55,%56,%57,%58,%59,%60,%61,%62,%63}, {%64,%65,%66,%67}, q, 0, 1, 1, 1;}"
    : "=f"(d[0]),"=f"(d[1]),"=f"(d[2]),"=f"(d[3]),"=f"(d[4]),"=f"(d[5]),"=f"(d[6]),"=f"(d[7]),"=f"(d[8]),"=f"(d[9]),"=f"(d[10]),"=f"(d[11]),"=f"(d[12]),"=f"(d[13]),"=f"(d[14]),"=f"(d[15]),"=f"(d[16]),"=f"(d[17]),"=f"(d[18]),"=f"(d[19]),"=f"(d[20]),"=f"(d[21]),"=f"(d[22]),"=f"(d[23]),"=f"(d[24]),"=f"(d[25]),"=f"(d[26]),"=f"(d[27]),"=f"(d[28]),"=f"(d[29]),"=f"(d[30]),"=f"(d[31]),"=f"(d[32]),"=f"(d[33]),"=f"(d[34]),"=f"(d[35]),"=f"(d[36]),"=f"(d[37]),"=f"(d[38]),"=f"(d[39]),"=f"(d[40]),"=f"(d[41]),"=f"(d[42]),"=f"(d[43]),"=f"(d[44]),"=f"(d[45]),"=f"(d[46]),"=f"(d[47]),"=f"(d[48]),"=f"(d[49]),"=f"(d[50]),"=f"(d[51]),"=f"(d[52]),"=f"(d[53]),"=f"(d[54]),"=f"(d[55]),"=f"(d[56]),"=f"(d[57]),"=f"(d[58]),"=f"(d[59]),"=f"(d[60]),"=f"(d[61]),"=f"(d[62]),"=f"(d[63])
    : "r"(a.x), "r"(a.y), "r"(a.z), "r"(a.w), "r"(off), "n"((uint32_t)DESC), "n"((uint32_t)(DESC >> 32)));
  if constexpr (!ZERO)
    asm volatile("{.reg .b32 l; .reg .b64 q; add.u32 l, %68, %69; mov.b64 q, {l, %70};\n"
    "wgmma.mma_async.sync.aligned.m64n128k16.f32.bf16.bf16 {%0,%1,%2,%3,%4,%5,%6,%7,%8,%9,%10,%11,%12,%13,%14,%15,%16,%17,%18,%19,%20,%21,%22,%23,%24,%25,%26,%27,%28,%29,%30,%31,%32,%33,%34,%35,%36,%37,%38,%39,%40,%41,%42,%43,%44,%45,%46,%47,%48,%49,%50,%51,%52,%53,%54,%55,%56,%57,%58,%59,%60,%61,%62,%63}, {%64,%65,%66,%67}, q, 1, 1, 1, 1;}"
    : "+f"(d[0]),"+f"(d[1]),"+f"(d[2]),"+f"(d[3]),"+f"(d[4]),"+f"(d[5]),"+f"(d[6]),"+f"(d[7]),"+f"(d[8]),"+f"(d[9]),"+f"(d[10]),"+f"(d[11]),"+f"(d[12]),"+f"(d[13]),"+f"(d[14]),"+f"(d[15]),"+f"(d[16]),"+f"(d[17]),"+f"(d[18]),"+f"(d[19]),"+f"(d[20]),"+f"(d[21]),"+f"(d[22]),"+f"(d[23]),"+f"(d[24]),"+f"(d[25]),"+f"(d[26]),"+f"(d[27]),"+f"(d[28]),"+f"(d[29]),"+f"(d[30]),"+f"(d[31]),"+f"(d[32]),"+f"(d[33]),"+f"(d[34]),"+f"(d[35]),"+f"(d[36]),"+f"(d[37]),"+f"(d[38]),"+f"(d[39]),"+f"(d[40]),"+f"(d[41]),"+f"(d[42]),"+f"(d[43]),"+f"(d[44]),"+f"(d[45]),"+f"(d[46]),"+f"(d[47]),"+f"(d[48]),"+f"(d[49]),"+f"(d[50]),"+f"(d[51]),"+f"(d[52]),"+f"(d[53]),"+f"(d[54]),"+f"(d[55]),"+f"(d[56]),"+f"(d[57]),"+f"(d[58]),"+f"(d[59]),"+f"(d[60]),"+f"(d[61]),"+f"(d[62]),"+f"(d[63])
    : "r"(a.x), "r"(a.y), "r"(a.z), "r"(a.w), "r"(off), "n"((uint32_t)DESC), "n"((uint32_t)(DESC >> 32)));
}

template <bool ZERO, uint64_t DESC> __device__ __forceinline__ void wgmma96(float* d, const uint4& a, uint32_t off) {
  if constexpr (ZERO)
    asm volatile("{.reg .b32 l; .reg .b64 q; add.u32 l, %52, %53; mov.b64 q, {l, %54};\n"
    "wgmma.mma_async.sync.aligned.m64n96k16.f32.bf16.bf16 {%0,%1,%2,%3,%4,%5,%6,%7,%8,%9,%10,%11,%12,%13,%14,%15,%16,%17,%18,%19,%20,%21,%22,%23,%24,%25,%26,%27,%28,%29,%30,%31,%32,%33,%34,%35,%36,%37,%38,%39,%40,%41,%42,%43,%44,%45,%46,%47}, {%48,%49,%50,%51}, q, 0, 1, 1, 1;}"
    : "=f"(d[0]),"=f"(d[1]),"=f"(d[2]),"=f"(d[3]),"=f"(d[4]),"=f"(d[5]),"=f"(d[6]),"=f"(d[7]),"=f"(d[8]),"=f"(d[9]),"=f"(d[10]),"=f"(d[11]),"=f"(d[12]),"=f"(d[13]),"=f"(d[14]),"=f"(d[15]),"=f"(d[16]),"=f"(d[17]),"=f"(d[18]),"=f"(d[19]),"=f"(d[20]),"=f"(d[21]),"=f"(d[22]),"=f"(d[23]),"=f"(d[24]),"=f"(d[25]),"=f"(d[26]),"=f"(d[27]),"=f"(d[28]),"=f"(d[29]),"=f"(d[30]),"=f"(d[31]),"=f"(d[32]),"=f"(d[33]),"=f"(d[34]),"=f"(d[35]),"=f"(d[36]),"=f"(d[37]),"=f"(d[38]),"=f"(d[39]),"=f"(d[40]),"=f"(d[41]),"=f"(d[42]),"=f"(d[43]),"=f"(d[44]),"=f"(d[45]),"=f"(d[46]),"=f"(d[47])
    : "r"(a.x), "r"(a.y), "r"(a.z), "r"(a.w), "r"(off), "n"((uint32_t)DESC), "n"((uint32_t)(DESC >> 32)));
  if constexpr (!ZERO)
    asm volatile("{.reg .b32 l; .reg .b64 q; add.u32 l, %52, %53; mov.b64 q, {l, %54};\n"
    "wgmma.mma_async.sync.aligned.m64n96k16.f32.bf16.bf16 {%0,%1,%2,%3,%4,%5,%6,%7,%8,%9,%10,%11,%12,%13,%14,%15,%16,%17,%18,%19,%20,%21,%22,%23,%24,%25,%26,%27,%28,%29,%30,%31,%32,%33,%34,%35,%36,%37,%38,%39,%40,%41,%42,%43,%44,%45,%46,%47}, {%48,%49,%50,%51}, q, 1, 1, 1, 1;}"
    : "+f"(d[0]),"+f"(d[1]),"+f"(d[2]),"+f"(d[3]),"+f"(d[4]),"+f"(d[5]),"+f"(d[6]),"+f"(d[7]),"+f"(d[8]),"+f"(d[9]),"+f"(d[10]),"+f"(d[11]),"+f"(d[12]),"+f"(d[13]),"+f"(d[14]),"+f"(d[15]),"+f"(d[16]),"+f"(d[17]),"+f"(d[18]),"+f"(d[19]),"+f"(d[20]),"+f"(d[21]),"+f"(d[22]),"+f"(d[23]),"+f"(d[24]),"+f"(d[25]),"+f"(d[26]),"+f"(d[27]),"+f"(d[28]),"+f"(d[29]),"+f"(d[30]),"+f"(d[31]),"+f"(d[32]),"+f"(d[33]),"+f"(d[34]),"+f"(d[35]),"+f"(d[36]),"+f"(d[37]),"+f"(d[38]),"+f"(d[39]),"+f"(d[40]),"+f"(d[41]),"+f"(d[42]),"+f"(d[43]),"+f"(d[44]),"+f"(d[45]),"+f"(d[46]),"+f"(d[47])
    : "r"(a.x), "r"(a.y), "r"(a.z), "r"(a.w), "r"(off), "n"((uint32_t)DESC), "n"((uint32_t)(DESC >> 32)));
}

template <bool ZERO, uint64_t DESC> __device__ __forceinline__ void wgmma64(float* d, const uint4& a, uint32_t off) {
  if constexpr (ZERO)
    asm volatile("{.reg .b32 l; .reg .b64 q; add.u32 l, %36, %37; mov.b64 q, {l, %38};\n"
    "wgmma.mma_async.sync.aligned.m64n64k16.f32.bf16.bf16 {%0,%1,%2,%3,%4,%5,%6,%7,%8,%9,%10,%11,%12,%13,%14,%15,%16,%17,%18,%19,%20,%21,%22,%23,%24,%25,%26,%27,%28,%29,%30,%31}, {%32,%33,%34,%35}, q, 0, 1, 1, 1;}"
    : "=f"(d[0]),"=f"(d[1]),"=f"(d[2]),"=f"(d[3]),"=f"(d[4]),"=f"(d[5]),"=f"(d[6]),"=f"(d[7]),"=f"(d[8]),"=f"(d[9]),"=f"(d[10]),"=f"(d[11]),"=f"(d[12]),"=f"(d[13]),"=f"(d[14]),"=f"(d[15]),"=f"(d[16]),"=f"(d[17]),"=f"(d[18]),"=f"(d[19]),"=f"(d[20]),"=f"(d[21]),"=f"(d[22]),"=f"(d[23]),"=f"(d[24]),"=f"(d[25]),"=f"(d[26]),"=f"(d[27]),"=f"(d[28]),"=f"(d[29]),"=f"(d[30]),"=f"(d[31])
    : "r"(a.x), "r"(a.y), "r"(a.z), "r"(a.w), "r"(off), "n"((uint32_t)DESC), "n"((uint32_t)(DESC >> 32)));
  if constexpr (!ZERO)
    asm volatile("{.reg .b32 l; .reg .b64 q; add.u32 l, %36, %37; mov.b64 q, {l, %38};\n"
    "wgmma.mma_async.sync.aligned.m64n64k16.f32.bf16.bf16 {%0,%1,%2,%3,%4,%5,%6,%7,%8,%9,%10,%11,%12,%13,%14,%15,%16,%17,%18,%19,%20,%21,%22,%23,%24,%25,%26,%27,%28,%29,%30,%31}, {%32,%33,%34,%35}, q, 1, 1, 1, 1;}"
    : "+f"(d[0]),"+f"(d[1]),"+f"(d[2]),"+f"(d[3]),"+f"(d[4]),"+f"(d[5]),"+f"(d[6]),"+f"(d[7]),"+f"(d[8]),"+f"(d[9]),"+f"(d[10]),"+f"(d[11]),"+f"(d[12]),"+f"(d[13]),"+f"(d[14]),"+f"(d[15]),"+f"(d[16]),"+f"(d[17]),"+f"(d[18]),"+f"(d[19]),"+f"(d[20]),"+f"(d[21]),"+f"(d[22]),"+f"(d[23]),"+f"(d[24]),"+f"(d[25]),"+f"(d[26]),"+f"(d[27]),"+f"(d[28]),"+f"(d[29]),"+f"(d[30]),"+f"(d[31])
    : "r"(a.x), "r"(a.y), "r"(a.z), "r"(a.w), "r"(off), "n"((uint32_t)DESC), "n"((uint32_t)(DESC >> 32)));
}

template <bool ZERO, uint64_t DESC> __device__ __forceinline__ void wgmma48(float* d, const uint4& a, uint32_t off) {
  if constexpr (ZERO)
    asm volatile("{.reg .b32 l; .reg .b64 q; add.u32 l, %28, %29; mov.b64 q, {l, %30};\n"
    "wgmma.mma_async.sync.aligned.m64n48k16.f32.bf16.bf16 {%0,%1,%2,%3,%4,%5,%6,%7,%8,%9,%10,%11,%12,%13,%14,%15,%16,%17,%18,%19,%20,%21,%22,%23}, {%24,%25,%26,%27}, q, 0, 1, 1, 1;}"
    : "=f"(d[0]),"=f"(d[1]),"=f"(d[2]),"=f"(d[3]),"=f"(d[4]),"=f"(d[5]),"=f"(d[6]),"=f"(d[7]),"=f"(d[8]),"=f"(d[9]),"=f"(d[10]),"=f"(d[11]),"=f"(d[12]),"=f"(d[13]),"=f"(d[14]),"=f"(d[15]),"=f"(d[16]),"=f"(d[17]),"=f"(d[18]),"=f"(d[19]),"=f"(d[20]),"=f"(d[21]),"=f"(d[22]),"=f"(d[23])
    : "r"(a.x), "r"(a.y), "r"(a.z), "r"(a.w), "r"(off), "n"((uint32_t)DESC), "n"((uint32_t)(DESC >> 32)));
  if constexpr (!ZERO)
    asm volatile("{.reg .b32 l; .reg .b64 q; add.u32 l, %28, %29; mov.b64 q, {l, %30};\n"
    "wgmma.mma_async.sync.aligned.m64n48k16.f32.bf16.bf16 {%0,%1,%2,%3,%4,%5,%6,%7,%8,%9,%10,%11,%12,%13,%14,%15,%16,%17,%18,%19,%20,%21,%22,%23}, {%24,%25,%26,%27}, q, 1, 1, 1, 1;}"
    : "+f"(d[0]),"+f"(d[1]),"+f"(d[2]),"+f"(d[3]),"+f"(d[4]),"+f"(d[5]),"+f"(d[6]),"+f"(d[7]),"+f"(d[8]),"+f"(d[9]),"+f"(d[10]),"+f"(d[11]),"+f"(d[12]),"+f"(d[13]),"+f"(d[14]),"+f"(d[15]),"+f"(d[16]),"+f"(d[17]),"+f"(d[18]),"+f"(d[19]),"+f"(d[20]),"+f"(d[21]),"+f"(d[22]),"+f"(d[23])
    : "r"(a.x), "r"(a.y), "r"(a.z), "r"(a.w), "r"(off), "n"((uint32_t)DESC), "n"((uint32_t)(DESC >> 32)));
}

__host__ __device__ constexpr int ph_n(int p) { return p == 0 ? 240 : p == 2 ? 224 : 160; }
__host__ __device__ constexpr int ph_steps(int p) { return p == 1 ? 20 : p == 3 ? 54 : 40; }
__host__ __device__ constexpr int ph_sps(int p) { return (p & 1) ? 3 : 2; }
__host__ __device__ constexpr int ph_own(int p) { return p == 3 ? 14 : 5; }
__host__ __device__ constexpr int ph_b0(int p) { return p == 0 ? 0 : p == 1 ? 20 : p == 2 ? 27 : 47; }
__host__ __device__ constexpr uint32_t b_off(int s) { return (s % NBS) * BSLOT; }
__host__ __device__ constexpr int b_dep(int s) { return s >= 10 ? s - 11 : s - 10; }
__host__ __device__ constexpr int b_infl(int s) {
  const int d = b_dep(s);
  return (d >= -6 && d < 2) || (d >= ph_b0(2) - 6 && d < ph_b0(2) + 2) ? INFL_X : INFL; }
__device__ __forceinline__ int h_start(int sl) { return sl < 7 ? 224 * sl : 1536; }
__device__ __forceinline__ int x_piece(int j, int i) { return (j & 1) ? (i == 4 ? 0 : i + 1) : i; }
__device__ __forceinline__ int step_k(int ph, int j, int i, int& av) {
  const int len = ph_own(ph), q = (ph & 1) ? j >> 1 : j, own = (ph == 3 && q == 3) ? 12 : len;
  int pos = i < own ? q * len + ((ph & 1) ? i : x_piece(j, i)) : (i - own < q * len ? i - own : i);
  if (((SWP >> ph) & 1) && i >= own) pos = i < len ? i - own : i / len == q ? i - q * len + len - own : i;
  const int c = pos / len, off = pos - c * len, sl = (ph & 1) ? 2 * c + (j & 1) : c;
  av = i == own - 1 ? 1 : ((ph == 3 && c == 3) ? 12 : len) - off;
  if (((SWP >> ph) & 1) && i >= own && i < len) av = len - i;
  return (ph == 3 ? h_start(sl) >> 4 : 5 * sl) + off;
}
__device__ __forceinline__ uint4 b_entry(uint32_t sb, int j, int rank, int bs) {
  const int ph = bs < 20 ? 0 : bs < 27 ? 1 : bs < 47 ? 2 : 3, sps = ph_sps(ph), role = (bs ^ rank) & 1;
  const int i0 = (bs - ph_b0(ph)) * sps, ns = min(sps, ph_steps(ph) - i0);
  int av, av1;
  int k0 = step_k(ph, j, i0, av), n1 = min(av, ns), n2 = ns - n1;
  const int k1 = step_k(ph, j, i0 + n1, av1), d = b_dep(bs);
  const int slab = ph == 0 ? (role ? 12 : 3) : ph == 2 ? 14 : 10;
  const int m0 = ph == 0 ? (role ? 0 : 2) : ph == 1 ? 4 : ph == 2 ? 7 : 9;
  uint32_t dst = sb + b_off(bs) + (ph == 0 && !role ? 12288 : 0);
  if (ph != 0) {
    if (!role) { dst += n1 * slab * 512; k0 = k1; n1 = n2; }
    n2 = 0;
  }
  const int c2 = ph == 0 ? 0 : ph == 2 ? h_start(j) >> 5 : 5 * (j >> 1);
  return make_uint4(dst, (k0 & 255) | ((k1 & 255) << 8) | (c2 << 16) | ((ph == 0 ? 5 * j + (role ? 0 : 4) : 0) << 24),
                    (n1 ? ((m0 + n1 - 1) << 7) | 0x8000u : 0u) | (b_infl(bs) << 16) | (n2 ? 0x80000000u : 0u),
                    ((ph == 0 ? 15 : slab) * ns * 512) | (slab << 16) | ((d < 0 ? d + 65 : d) << 20) | (d < 0 ? 0x80000000u : 0u));
}

struct Ctx {
  uint32_t sb, eb, w, wi, lane, layer;
  int j;
};
struct LN { float rs0, nm0, rs1, nm1; };

__host__ __device__ constexpr int grp_start(int p, int k) {
  if (p == 1) return k == 0 ? 5 : 20;
  const int g = p == 3 ? GH : GX, n = (ph_steps(p) - ph_own(p) + g - 1) / g;
  return k == 0 ? ph_own(p) : k >= n ? ph_steps(p) : ph_steps(p) - g * (n - k); }
__host__ __device__ constexpr int grp_of(int p, int i) { int k = 0; while (grp_start(p, k + 1) <= i) k++; return k; }
__host__ __device__ constexpr bool is_check(int p, int i) { return i >= ph_own(p) && (i == grp_start(p, grp_of(p, i)) || (p == 1 && i % 5 == 0)); }
__host__ __device__ constexpr int ph_tail(int p) { return p == 0 ? 40 : p == 1 ? T1 : p == 2 ? T2 : T3; }

static_assert(grp_start(0, 1) == 10 && IH < 12 && INFL <= FIRST, "schedule");

template <int I> struct IC { static constexpr int v = I; };
template <int B, int E, class F> __device__ __forceinline__ void static_for(F&& f) {
  if constexpr (B < E) { f(IC<B>{}); static_for<B + 1, E>(f); } }

template <int PH, int PART, int i>
__device__ __forceinline__ void mma_step(float* acc, const uint4& a, uint32_t r) {
  constexpr int SPS = ph_sps(PH);
  constexpr uint32_t base = SB0 + b_off(ph_b0(PH) + i / SPS);
  constexpr uint64_t D128 = ((uint64_t)(2048 >> 4) << 16) | ((uint64_t)(1024 >> 4) << 32) | (1ull << 62);
  constexpr uint64_t D64 = ((uint64_t)(1024 >> 4) << 16) | ((uint64_t)(512 >> 4) << 32) | (2ull << 62);
  constexpr uint64_t D32 = ((uint64_t)(512 >> 4) << 16) | ((uint64_t)(256 >> 4) << 32) | (3ull << 62);
  constexpr bool Z = i == 0;
  if constexpr (PH == 0) {
    constexpr uint32_t mn = base + (i % 2) * 6144, rm = base + 12288 + (i % 2) * 1536;
    wgmma192<Z, D128 | (mn >> 4)>(acc, a, 0);
    wgmma48<Z, D32 | (rm >> 4)>(acc + 96, a, 0);
  } else if constexpr (PH == 2) {
    constexpr uint32_t sl = base + (i % 2) * 7168;
    if constexpr (PART != 1) wgmma128<Z, D64 | (sl >> 4)>(acc, a, 0);
    if constexpr (PART != 0) wgmma96<Z, D64 | ((sl + 4096) >> 4)>(acc + 64, a, 0);
  } else {
    constexpr uint32_t sl = base + (i % 3) * 5120;
    if constexpr (PART != 1) wgmma96<Z, D64 | (sl >> 4)>(acc, a, (r ^ 1) * 128);
    if constexpr (PART != 0) wgmma64<Z, D64 | (sl >> 4)>(acc + 48, a, r * 192);
  }
}

template <int PH, class Side, class Early>
__device__ __forceinline__ void mainloop(float (&acc)[ph_n(PH) / 2], uint4 (&own)[ph_own(PH)], const uint4* src, uint32_t tag, Ctx& c,
                                         float2* gst, const uint32_t (&x0)[5], LN& ln, Side side, Early early) {
  constexpr int SPS = ph_sps(PH), NST = ph_steps(PH), NS = (NST + SPS - 1) / SPS, OWN = ph_own(PH), B0 = ph_b0(PH);
  constexpr int TL = ph_tail(PH), TS = TL == NST ? NS : TL / SPS;
  constexpr int I0 = PH == 1 ? IO : PH == 3 ? IH : IX;
  constexpr int LD = (LEADS >> (4 * PH)) & 15;
  constexpr bool STATS = !(PH & 1);
  constexpr uint32_t MASK = 1u;
  constexpr int O12 = PH == 3 ? 12 : 0, O13 = PH == 3 ? 13 : 0;
  const bool el0 = c.lane < 2, el1 = c.lane + 32 * c.layer < 2;
  auto release = [&](int s) { mbar_arrive_cl_if(c.eb + (B0 + s) * 8, B0 + s >= 54 ? el1 : el0); };
  const int q = (PH & 1) ? c.j >> 1 : c.j;
  const uint32_t r = c.j & 1;
  const bool sf = PH == 3 && q == 3;
  const uint4* seg[8];
  uint4 a[NST], sv0, sv1;
  auto probe = [&](int z0) {
    constexpr int NPR = PH == 1 ? 3 : PH == 3 ? 1 : 2, PO = PH == 3 ? HPROBE : 4;
    uint32_t bad;
    do {
      bad = 0;
#pragma unroll
      for (int z = z0; z < z0 + NPR; z++) {
        uint32_t v;
        asm volatile("ld.relaxed.gpu.global.u32 %0, [%1];" : "=r"(v) : "l"(src + ((((SWP >> PH) & 1) ? (z + 1 == q ? 0 : z + 1) : z + (z >= q)) * OWN + PO) * 128 + 31 - (int)c.lane) : "memory");
        bad |= v ^ tag;
      }
    } while (__any_sync(~0u, bad & MASK));
  };
  auto issue = [&](auto K) {
    constexpr int k = decltype(K)::v, gb = grp_start(PH, k), ge = grp_start(PH, k + 1);
#pragma unroll
    for (int i = gb; i < ge; i++)
      if (i % OWN == 0) { seg[i / OWN] = ((SWP >> PH) & 1) ? src - (i / OWN == q ? (i - (PH == 3 && i == 42 ? 2 : 0)) * 128 : 0) : src - (i / OWN <= q ? (sf ? 12 : OWN) * 128 : 0); asm volatile("" : "+l"(seg[i / OWN])); }
    if (PH == 0 && k == 0 && c.layer == 0) {
      mbar_wait(c.sb + BAR_X2 + 8 * c.w, 0);
#pragma unroll
      for (int i = gb; i < ge; i++) ldsm4(c.sb + OFF_XCH + c.w * 10240 + (c.wi * 16 + (c.lane & 15)) * 160 + (c.lane >> 4) * 16 + (i - gb) * 32, a[i]);
#pragma unroll
      for (int i = gb; i < ge; i++) shift_rows(a[i], x0[3], x0[4]);
    } else {
      if (PH == 0 && k == 1) { if (c.layer == 0) probe(1); }
      if (PH == 1 && k == 0) probe(0);
      if (PH == 3 && k == 0) { if (c.layer == 0) probe(0); }
#pragma unroll
      for (int i = gb; i < ge; i++) a[i] = ldg_strong(seg[i / OWN] + i * 128);
    }
    if (STATS && ge == NST) { sv0 = ldg_strong(gst + 2 * (c.lane & 3)); sv1 = ldg_strong(gst + 64 + 2 * (c.lane & 3)); }
  };
  auto late_tag = [&]() {
    uint32_t tz;
    asm volatile("{.reg .u32 h; mov.u32 h, %%clock_hi; shr.u32 h, h, 31; xor.b32 %0, h, %1;}" : "=r"(tz) : "r"(tag));
    return tz;
  };
  float s0 = 0.f, q0 = 0.f, s1 = 0.f, q1 = 0.f, sh[4];
  mbar_wait(c.sb + BAR_FULLB + B0 * 8, c.layer);
  wg_fence();
  static_for<0, NST>([&](auto I) {
    constexpr int i = decltype(I)::v, s = i / SPS, gi = grp_of(PH, i);
    constexpr bool last = (i + 1) % SPS == 0 || i + 1 == NST;
    if (PH == 3 && i == 12) {
      if (sf) {
        const uint32_t tz = late_tag();
        while (__any_sync(~0u, ((own[O12].x ^ tz) | (own[O13].x ^ tz)) & MASK)) { own[O12] = ldg_strong(src); own[O13] = ldg_strong(src + 128); }
      }
      wg_fence();
    }
    if constexpr (is_check(PH, i)) {
      constexpr int CH = PH == 1 ? 5 : 64;
      constexpr int ge = grp_start(PH, gi + 1), ce = i + CH < ge ? i + CH : ge;
      const uint32_t tz = late_tag();
      while (true) {
        if (!stale<ce - i>(&a[i], tz, PH == 0 && gi == 0 ? c.layer : MASK)) break;
#pragma unroll
        for (int z = i; z < ge; z++) a[z] = ldg_strong(seg[z / OWN] + z * 128);
      }
      wg_fence();
    }
    if constexpr (STATS) {
      constexpr int G0 = grp_start(PH, grp_of(PH, NST - 1));
      if constexpr (i == G0) {
        while (__any_sync(~0u, ((sv0.x ^ tag) | (sv0.z ^ tag) | (sv1.x ^ tag) | (sv1.z ^ tag)) & 1)) {
          sv0 = ldg_strong(gst + 2 * (c.lane & 3)); sv1 = ldg_strong(gst + 64 + 2 * (c.lane & 3));
        }
        wg_fence();
        q0 = __uint_as_float(sv0.x) + __uint_as_float(sv0.z); s0 = __uint_as_float(sv0.y) + __uint_as_float(sv0.w);
        q1 = __uint_as_float(sv1.x) + __uint_as_float(sv1.z); s1 = __uint_as_float(sv1.y) + __uint_as_float(sv1.w);
      }
      if constexpr (i == G0 + 2 || i == G0 + 4) { s0 += sh[0]; q0 += sh[1]; s1 += sh[2]; q1 += sh[3]; }
      if constexpr (i == G0 || i == G0 + 2) {
        constexpr int x = i == G0 ? 1 : 2;
        sh[0] = __shfl_xor_sync(~0u, s0, x); sh[1] = __shfl_xor_sync(~0u, q0, x); sh[2] = __shfl_xor_sync(~0u, s1, x); sh[3] = __shfl_xor_sync(~0u, q1, x);
      }
      if constexpr (i == G0 + 4) {
        ln.nm0 = s0 * (-1.f / 640.f); ln.nm1 = s1 * (-1.f / 640.f);
        ln.rs0 = rsq(fmaxf(fmaf(q0, 1.f / 640.f, -ln.nm0 * ln.nm0), 0.f) + 1e-5f);
        ln.rs1 = rsq(fmaxf(fmaf(q1, 1.f / 640.f, -ln.nm1 * ln.nm1), 0.f) + 1e-5f);
      }
    }
    const uint32_t fbn = c.sb + BAR_FULLB + (B0 + s + 1) * 8;
    uint32_t okb = 1;
    if (last && s + 1 < NS) okb = mbar_peek(fbn, c.layer);
    mma_step<PH, (i < TL ? -1 : 0), i>(acc, i < OWN ? own[i < OWN ? i : 0] : a[i], r);
    if (last) wg_commit();
    if (i == I0) issue(IC<0>{});
    if (PH == 3 && i == I0) { if (sf) { own[O12] = ldg_strong(src); own[O13] = ldg_strong(src + 128); } }
    constexpr bool iss = i >= OWN && i == grp_start(PH, gi) && grp_start(PH, gi + 1) < NST;
    if constexpr (iss) issue(IC<gi + 1>{});
    if (last) {
      if (s >= 1 && s <= TS) {
        wg_wait<1>();
        release(s - 1);
      }
      if (STATS) {
        if (s < 5) {
          const uint4 v = own[s < 5 ? s : 0];
          const uint32_t park = c.sb + OFF_LAND + (c.w * 4 + c.wi) * 2560 + c.lane * 16 + s * 512;
          if (PH == 0)
            asm volatile("{.reg .pred p; setp.ne.u32 p, %6, 0; @p st.shared.v4.u32 [%0], {%1,%2,%3,%4}; @p st.shared.u32 [%0], %5;}"
                         ::"r"(park), "r"(v.x), "r"(v.y), "r"(v.z), "r"(v.w), "r"(x0[s < 5 ? s : 0]), "r"(c.layer) : "memory");
          else { sts4u(park, v); sts1u(park, x0[s < 5 ? s : 0]); }
          const float e0 = blo(v.x), e1 = bhi(v.x), e2 = blo(v.z), e3 = bhi(v.z), f0 = blo(v.y), f1 = bhi(v.y), f2 = blo(v.w), f3 = bhi(v.w);
          s0 += (e0 + e1) + (e2 + e3); q0 = fmaf(e0, e0, fmaf(e1, e1, fmaf(e2, e2, fmaf(e3, e3, q0))));
          s1 += (f0 + f1) + (f2 + f3); q1 = fmaf(f0, f0, fmaf(f1, f1, fmaf(f2, f2, fmaf(f3, f3, q1))));
          asm volatile("" : "+f"(s0), "+f"(q0), "+f"(s1), "+f"(q1));
        }
        if (s == 5) {
          const bool hi = c.lane & 1;
          float sa = hi ? s1 : s0, qa = hi ? q1 : q0;
          sa += __shfl_xor_sync(~0u, hi ? s0 : s1, 1); qa += __shfl_xor_sync(~0u, hi ? q0 : q1, 1);
          sa += __shfl_xor_sync(~0u, sa, 2); qa += __shfl_xor_sync(~0u, qa, 2);
          asm volatile("{.reg .pred p; .reg .b64 u; setp.eq.u32 p, %3, 0; mov.b64 u, {%1,%2}; @p st.relaxed.gpu.global.b64 [%0], u;}"
                       ::"l"(gst + (hi ? 64 : 0) + c.j), "r"((__float_as_uint(qa) & ~1u) | tag), "f"(sa), "r"(c.lane & 2) : "memory");
        }
        if constexpr (STATS) side(IC<s>{});
        if (s == NS - 2 && c.layer == 0) mbar_wait(c.sb + BAR_CS + 4 * PH, 0);
      }
      if (LD > 0 && s + 1 == NS - LD) mbar_wait_unless(c.w ^ 1, c.sb + BAR_LEAD + 8 * PH, c.layer);
      if (s + 1 < NS) {
        mbar_wait_unless(okb, fbn, c.layer);
      }
      wg_fence();
    } else if (i == I0 || iss) wg_fence();
  });
  STAMP(c.w, 96 + 4 * c.layer + PH);
  if constexpr (TL == NST) {
    if (LD > 0) mbar_arrive_if(c.sb + BAR_LEAD + 8 * PH, threadIdx.x == 0);
    early(IC<-1>{});
    wg_wait<0>();
    release(NS - 1);
    static_for<0, 16>(early);
  } else {
    static_for<TL, NST>([&](auto I) {
      constexpr int i = decltype(I)::v, s = i / SPS;
      constexpr bool last = (i + 1) % SPS == 0 || i + 1 == NST;
      mma_step<PH, 1, i>(acc, i < OWN ? own[i < OWN ? i : 0] : a[i], r);
      wg_commit();
      if (LD > 0 && i + 1 == NST) mbar_arrive_if(c.sb + BAR_LEAD + 8 * PH, threadIdx.x == 0);
      if constexpr (i == TL) early(IC<-1>{});
      if constexpr (i == TL + 1) { wg_wait<2>(); early(IC<0>{}); }
      if (last && s >= TS + 2 && i + 1 < NST) { wg_wait<2 * SPS>(); release(s - 2); }
      if constexpr (i >= TL + 2) early(IC<i - TL - 1>{});
      wg_fence();
    });
    wg_wait<0>();
#pragma unroll
    for (int s = (NS - 3 > TS ? NS - 3 : TS); s < NS; s++) release(s);
    static_for<NST - TL - 1, 16>(early);
  }
}

__device__ __forceinline__ constexpr int blk(int part, int e) { return e < 8 ? 8 * part + e : 24 + 2 * part + (e - 8); }
__device__ __forceinline__ constexpr int kpos(int e) { return e == 2 ? 18 : e == 7 ? 19 : 4 * (2 * (e / 5) + (e % 5) / 3) + 2 + (e % 5) % 3; }
__device__ __forceinline__ constexpr int vpos(int e) { return 4 * (e >> 1) + (e & 1); }
__device__ __forceinline__ uint32_t& word(uint4& v, int i) { return i == 0 ? v.x : i == 1 ? v.y : i == 2 ? v.z : v.w; }

__device__ __forceinline__ float strip_reduce(float (&s)[8], int lane) {
#pragma unroll
  for (int i = 0; i < 4; i++) { const bool hi = lane & 16; const float snd = hi ? s[i] : s[i + 4], kp = hi ? s[i + 4] : s[i]; s[i] = kp + __shfl_xor_sync(~0u, snd, 16); }
#pragma unroll
  for (int i = 0; i < 2; i++) { const bool hi = lane & 8; const float snd = hi ? s[i] : s[i + 2], kp = hi ? s[i + 2] : s[i]; s[i] = kp + __shfl_xor_sync(~0u, snd, 8); }
  const bool hi = lane & 4;
  const float snd = hi ? s[0] : s[1], kp = hi ? s[1] : s[0];
  return kp + __shfl_xor_sync(~0u, snd, 4);
}

__device__ __forceinline__ float strip_part(uint32_t sb, int i0, int i1, int lane) {
  float v[8];
#pragma unroll
  for (int i = 0; i < 8; i++) v[i] = 0.f;
#pragma unroll 1
  for (int i = i0; i < i1; i++) {
    uint4 u[4];
#pragma unroll
    for (int z = 0; z < 4; z++) u[z] = lds4u(sb + OFF_CSB + i * 2048 + z * 512 + lane * 16);
#pragma unroll
    for (int z = 0; z < 4; z++) {
      v[2 * z] += (blo(word(u[0], z)) + blo(word(u[1], z))) + (blo(word(u[2], z)) + blo(word(u[3], z)));
      v[2 * z + 1] += (bhi(word(u[0], z)) + bhi(word(u[1], z))) + (bhi(word(u[2], z)) + bhi(word(u[3], z)));
    }
  }
  return strip_reduce(v, lane);
}

__global__ void __cluster_dims__(2, 1, 1) __launch_bounds__(384, 1) mega_kernel(const Ptrs P, const __grid_constant__ Maps M) {
  const uint32_t sb = s2u(smem_raw);
  if ((sb & 0x3FFFF) != SB0) __trap();
  const int tid = threadIdx.x, lane = tid & 31;
  const int warp = __shfl_sync(~0u, tid >> 5, 0);
  const int bid = blockIdx.x;
  const int rank = bid & 1, cl = bid >> 1, i1 = cl - 4, i2 = cl - 36;
  const int m = 2 * (cl < 4 ? 0 : cl < 36 ? i1 & 7 : 1 + i2 % 7) + rank;
  const int j = cl < 4 ? cl : cl < 36 ? (i1 >> 3) + ((i1 & 7) ? 0 : 4) : 4 + i2 / 7;

  if (warp >= 8) {
    asm volatile("setmaxnreg.dec.sync.aligned.u32 40;");
    if (warp == 8) {
      auto x_tile = [&](uint32_t dst, uint32_t bar, int sl, int w) { mbar_expect(bar, 10240); tma3d(dst, &M.tx, 80 * sl, w, 64 * m, bar); };
      if (elect()) {
#pragma unroll
        for (int i = 0; i < 4; i++) mbar_init(sb + BAR_X + i * 8, 1);
#pragma unroll
        for (int i = 0; i < FIRST; i++) mbar_init(sb + BAR_FULLB + i * 8, 1);
        asm volatile("fence.mbarrier_init.release.cluster;" ::: "memory");
        x_tile(sb + OFF_LAND, sb + BAR_X, j, 0);
      }
      __syncwarp();
      asm volatile("bar.arrive 0, 384;" ::: "memory");
      cluster_arrive();
      if (elect()) {
#pragma unroll 1
        for (int i = 0; i < 2 * FIRST; i++) {
          const uint32_t dst = sb + (i >> 1) * BSLOT, fb = sb + BAR_FULLB + 8 * (i >> 1);
          const int k = i < 5 ? 5 * j + x_piece(j, i) : ((SWP & 1) ? j == 1 : j > 0) ? i - 5 : i;
          if (!(i & 1)) mbar_expect(fb, 15360);
          tma4d(dst + (i & 1) * 6144, &M.tw[0], 80 * j, 0, k, fb);
          tma4d(dst + 12288 + (i & 1) * 1536, &M.tw[2], 80 * j + 64, 0, k, fb);
          if (i == 1) x_tile(sb + OFF_LAND + 10240, sb + BAR_X + 8, j, 1);
          STAMP(3, 33 + (i >> 1));
        }
#pragma unroll
        for (int w = 0; w < 2; w++) x_tile(sb + OFF_XCH + w * 10240, sb + BAR_X2 + 8 * w, (SWP & 1) ? j != 1 : j == 0, w);
      }
      __syncwarp();
      bar_sync(4, 96);
      cluster_wait();
      if (elect()) {
        uint4 nx = lds4u(sb + OFF_TB + FIRST * 16);
#pragma unroll 1
        for (int layer = 0; layer < 2; layer++) {
#pragma unroll 1
          for (int bs = layer ? 0 : FIRST; bs < 65; bs++) {
            const uint4 q = nx;
            nx = lds4u(sb + OFF_TB + (bs == 64 ? 0 : bs + 1) * 16);
            const uint32_t fb = sb + BAR_FULLB + 8 * bs, prev = q.w >> 31;
            const int c0 = (q.y >> 24) * 16, c2 = (q.y >> 16) & 255;
            if (layer >= (int)prev) mbar_wait(sb + BAR_EMPTYB + ((q.w >> 20) & 127) * 8, layer ^ prev);
            { const int nf = layer == 0 && bs < 11 ? INFL : (q.z >> 16) & 15; mbar_wait(bs >= nf ? fb - 8 * nf : fb + 8 * (65 - nf), bs >= nf ? layer : 0); }
            mbar_expect(fb, q.w & 0xffff);
            const uint8_t* tm = (const uint8_t*)M.tw + (q.z & 0x7fff);
            if (q.z & 0x8000) tma4d_mc(q.x, tm, c0, c2, q.y & 255, fb);
            if (q.z >> 31) tma4d_mc(q.x + ((q.w >> 7) & 0x1e00), tm, c0, c2, (q.y >> 8) & 255, fb);
          }
        }
      }
    } else if (warp == 9) {
      if (elect()) {
        asm volatile("prefetch.tensormap [%0];" ::"l"(&M.tw[0]) : "memory");
        asm volatile("prefetch.tensormap [%0];" ::"l"(&M.tw[2]) : "memory");
      }
      __syncwarp();
      bar_sync(0, 384);
      cluster_arrive();
      if (lane >= 1 && lane < 15) asm volatile("prefetch.tensormap [%0];" ::"l"(&M.tw[lane]) : "memory");
      if (PS == 3) {
        __syncwarp();
        mbar_wait(sb + BAR_STRIP, 0);
        sts1u(sb + OFF_CSP + 128 + lane * 4, __float_as_uint(strip_part(sb, 7, 10, lane)));
        __syncwarp();
        if (lane == 0) mbar_arrive(sb + BAR_CSP);
      }
    } else {
      if (elect()) {
#pragma unroll
        for (int i = 0; i < 55; i++) mbar_init(sb + BAR_FULLB + (20 + (warp - 10) * 55 + i) * 8, i < 45 && warp == 10 ? 1 : 16);
        if (warp == 10) {
#pragma unroll
          for (int i = 0; i < 9; i++) mbar_init(sb + BAR_CS + i * 8, i < 7 ? 1 : i == 7 && PS ? PS - 1 : 8);
        } else {
#pragma unroll
          for (int i = FIRST; i < 20; i++) mbar_init(sb + BAR_FULLB + i * 8, 1);
        }
        asm volatile("fence.mbarrier_init.release.cluster;" ::: "memory");
      }
      __syncwarp();
      STAMP(2, 44);
      bar_sync(0, 384);
      cluster_arrive();
      const uint32_t tag = *(volatile uint32_t*)&P.s->epoch[bid] + 1;
#pragma unroll 1
      for (int i = tid - 320; i < 65; i += 64) sts4u(sb + OFF_TB + i * 16, b_entry(sb, j, rank, i));
      asm volatile("bar.arrive 4, 96;" ::: "memory");
      STAMP(2, 45);
      if (warp == 11) {
        cluster_wait();
        if (PS) {
          mbar_wait_bounded(sb + BAR_STRIP, 0);
          sts1u(sb + OFF_CSP + lane * 4, __float_as_uint(strip_part(sb, PS == 3 ? 4 : 5, PS == 3 ? 7 : 10, lane)));
          __syncwarp();
          if (lane == 0) mbar_arrive(sb + BAR_CSP);
        }
        mbar_wait_bounded(sb + BAR_CS, 0);
        if (lane == 0) P.s->epoch[bid] = tag;
        mbar_wait_bounded(sb + BAR_DONE, 0);
      } else {
        uint2* const cp = &P.s->cs[rank * 2048 + 32 * cl];
        cp[(lane & 3) * 8 + (lane >> 2)] = cp[4096 + (lane & 3) * 8 + (lane >> 2)] = make_uint2(0, tag - 1);
#pragma unroll 1
        for (int mat = 0; mat < 2; mat++) {
          float t;
          if (mat == 1) {
            mbar_wait(sb + BAR_EMPTYB + 8 * PF1, 0);
            if (lane == 0) l2_prefetch((const uint8_t*)P.w2 + bid * 17280, 17280);
          }
          mbar_wait(sb + BAR_EMPTYB + 8 * (mat ? ph_b0(1) : 1), 0);
          if (lane == 0) {
            asm volatile("fence.proxy.async.shared::cta;" ::: "memory");
            mbar_expect(sb + BAR_STRIP, 20480);
            tma2d(sb + OFF_CSB, &M.tc[mat], 32 * cl, 320 * rank, sb + BAR_STRIP);
            tma2d(sb + OFF_CSB + 10240, &M.tc[mat], 32 * cl, 320 * rank + 160, sb + BAR_STRIP);
          }
          const int cl_ = (lane & 3) * 8 + (lane >> 2);
          if (mat == 0 && !PS) {
            mbar_wait(sb + BAR_CSP, 0);
            const float* pp = (const float*)(smem_raw + OFF_CSP) + cl_;
            t = ((pp[0] + pp[32]) + (pp[64] + pp[96])) + ((pp[128] + pp[160]) + (pp[192] + pp[224]));
          } else {
            mbar_wait(sb + BAR_STRIP, mat);
            t = strip_part(sb, 0, mat ? 10 : PS == 3 ? 4 : 5, lane);
            if (mat == 0) {
              mbar_wait(sb + BAR_CSP, 0);
              const float* pp = (const float*)(smem_raw + OFF_CSP) + lane;
              t += PS == 3 ? pp[0] + pp[32] : pp[0];
            }
          }
          asm volatile("{.reg .b64 u; mov.b64 u, {%1,%2}; st.relaxed.gpu.global.b64 [%0], u;}"
                       ::"l"(cp + mat * 4096 + cl_), "f"(t), "r"(tag) : "memory");
          STAMP(2, 34 + 3 * mat);
          if (mat == 0) {
            if (lane == 0) { l2_prefetch((const uint8_t*)P.w1 + bid * 17280, 17280); l2_prefetch((const uint8_t*)M.wo + bid * 6400, 6400); }
          }
          const int ncol = mat == 0 ? 240 : (j < 6 ? 224 : 192);
#pragma unroll 1
          for (int i2 = 0; i2 < 4; i2 += 2) {
            while (true) {
              bool ok = true;
#pragma unroll
              for (int i = i2; i < i2 + 2; i++) {
                const int cc = i * 64 + lane * 2;
                const int col = mat ? h_start(j) + cc : i < 3 ? i * 640 + 80 * j + lane * 2 : (lane >> 3) * 640 + 80 * j + 64 + (lane & 7) * 2;
                uint4 q0 = make_uint4(0, tag, 0, tag), q1 = q0;
                if (cc < ncol) { q0 = ldg_strong(&P.s->cs[mat * 4096 + col]); q1 = ldg_strong(&P.s->cs[mat * 4096 + 2048 + col]); }
                ok = ok && q0.y == tag && q0.w == tag && q1.y == tag && q1.w == tag;
                sts2u(sb + OFF_CS + mat * 1024 + (cc >> 4) * 64 + ((cc >> 1) & 3) * 16 + (cc & 8),
                      __float_as_uint(__uint_as_float(q0.x) + __uint_as_float(q1.x)), __float_as_uint(__uint_as_float(q0.z) + __uint_as_float(q1.z)));
              }
              if (__all_sync(~0u, ok)) break;
              __nanosleep(100);
            }
          }
          asm volatile("fence.acq_rel.cta;" ::: "memory");
          __syncwarp();
          if (lane == 0) mbar_arrive(sb + BAR_CS + 8 * mat);
          STAMP(2, 40 + mat);
        }
      }
    }
  } else {
    uint4 xr[5];
    uint32_t x0[5];
    {
      const int w = warp >> 2, wi = warp & 3;
      asm volatile("setmaxnreg.inc.sync.aligned.u32 232;");
      bar_sync(0, 384);
      cluster_arrive();
      uint4* gx = P.s->x + ((2 * m + w) * 40 + 5 * j) * 128 + (tid & 127);
      stg_strong(gx + 4 * 128, make_uint4(0, 0, 0, 0));
      auto row_shift = [&](int row) {
        const uint2 v = __ldg((const uint2*)(P.x + (size_t)(128 * m + 2 * row + w) * D_));
        const float e = blo(v.x), d = fmaxf(fmaxf(fabsf(bhi(v.x) - e), fabsf(blo(v.y) - e)), fabsf(bhi(v.y) - e));
        return d < 0.5f * fabsf(e) ? (v.x & 0xffffu) * 0x10001u : 0u;
      };
      const uint32_t c0 = row_shift(wi * 16 + (lane >> 2)), c1 = row_shift(wi * 16 + 8 + (lane >> 2));
      STAMP(w, 34);
      const uint32_t stg = sb + OFF_LAND + warp * 2560;
      mbar_wait(sb + BAR_X + 8 * w, 0);
      STAMP(w, 33);
#pragma unroll
      for (int i = 0; i < 5; i++) ldsm4(stg + (lane & 15) * 160 + (lane >> 4) * 16 + x_piece(j, i) * 32, xr[i]);
#pragma unroll
      for (int i = 0; i < 5; i++) {
        sts4u(stg + i * 512 + lane * 16, xr[i]);
        shift_rows(xr[i], c0, c1);
        x0[i] = i == 4 ? c1 : c0;
        xr[i].x |= 1;
        stg_strong(gx + x_piece(j, i) * 128, xr[i]);
      }
      cluster_wait();
      STAMP(w, 1);
      if (warp == 0) GSTAMP(1);
    }
    const int g = lane >> 2, t = lane & 3;
    const uint32_t csa = sb + OFF_CS + 16 * t;
    auto ldcs = [&](int pair) { const uint4 v = lds4u(csa + pair * 64); return make_float4(__uint_as_float(v.x), __uint_as_float(v.y), __uint_as_float(v.z), __uint_as_float(v.w)); };
    Ctx c; c.sb = sb; c.eb = mapa(sb + BAR_EMPTYB, lane & 1); c.lane = lane;
#pragma unroll 1
    for (int hl_ = 0; hl_ < 4; hl_++) {
      const int hw = __shfl_sync(~0u, hl_ | (warp << 8) | (j << 12), 0), hl = hw & 255, layer = hl >> 1;
      const int w = (hw >> 10) & 1, wi = (hw >> 8) & 3, u = 2 * m + w, jj = hw >> 12, t128 = wi * 32 + lane;
      c.w = w; c.wi = wi; c.layer = layer; c.j = jj;
      float acc2[80];
      float os0 = 1.f, os1 = 1.f;
      LN ln;
      float2* const gst = P.s->st + (u * 64 + wi * 16 + g) * 8;
      const uint4* const gx = P.s->x + u * (40 * 128) + t128;
      const uint32_t lbase = sb + OFF_LAND + (w * 4 + wi) * 2560, land = lbase + lane * 16, ptag = (hl & 1) ^ 1;
      uint4 *gp, *gs, *gs2, *gxa, *gxb;
      uint4 pv[5];
      float rz[40];
      auto send = [&](auto C) {
        constexpr int cc = decltype(C)::v, ch = cc >= 0 && cc < 5 ? (cc + 1) % 5 : cc;
        const bool r = jj & 1;
        if constexpr (cc == -1) {
          gp = opaque(P.s->part + (u * 8 + jj) * 640 + t128);
          gs = pinned(gp + (r ? -5 : 3) * 128);
          gs2 = pinned(gp + (r ? -5 : 8) * 128);
        }
        if constexpr (cc == XRAT + 2) {
          gxa = opaque(P.s->x + (u * 40 + 5 * jj + r) * 128 + t128);
          gxb = opaque(gxa + (r ? -1 : 4) * 128);
        }
        if constexpr (cc >= XRAT + 2 && cc < XRAT + 7) {
          constexpr int i = cc - XRAT - 2;
#pragma unroll
          for (int z = 0; z < 4; z++) { rz[8 * i + 2 * z] = blo(word(xr[i], z)); rz[8 * i + 2 * z + 1] = bhi(word(xr[i], z)); asm volatile("" : "+f"(rz[8 * i + 2 * z]), "+f"(rz[8 * i + 2 * z + 1])); }
        }
        if constexpr (cc == XRAT) {
#pragma unroll
          for (int i = 0; i < 5; i++) xr[i] = lds4u(land + i * 512);
        }
        if constexpr (cc >= 0 && cc < 5) {
          constexpr int so = ch == 0 ? 0 : 8 * ch;
          float v[8];
#pragma unroll
          for (int z = 0; z < 8; z++) v[z] = ch > 0 ? acc2[so + z] : r ? acc2[z] : acc2[40 + z];
          stg_strong((ch < 2 ? gs2 : gs) + ch * 128, make_uint4(tagged(pack2(v[0], v[1]), ptag), pack2(v[2], v[3]), pack2(v[4], v[5]), pack2(v[6], v[7])));
        }
        if constexpr (cc == 5) {
#pragma unroll
          for (int z = 0; z < 8; z++) acc2[z] = r ? acc2[40 + z] : acc2[z];
        }
        if constexpr (cc == PVAT) {
#pragma unroll
          for (int i = 0; i < 5; i++) pv[i] = ldg_strong(gp + i * 128);
        }
      };
      if (!(hl & 1)) {
        float acc[120];
        uint32_t Kl[10], Vl[10], Ql[10], Qh[10];
        uint4 kvh[5], kvp[5];
#define KH(e) word(kvh[kpos(e) >> 2], kpos(e) & 3)
#define VH(e) word(kvh[vpos(e) >> 2], vpos(e) & 3)
#define KP(e) word(kvp[kpos(e) >> 2], kpos(e) & 3)
#define VP(e) word(kvp[vpos(e) >> 2], vpos(e) & 3)
        float4 ck[5], cv[5], cq[5];
        uint4* const xs = (uint4*)(smem_raw + OFF_XCH + w * 7680 + wi * 2560);
        uint4* const hp = P.s->halo + ((layer * 32 + u) * 8 + jj) * 160;
        mainloop<0>(acc, xr, gx, 1, c, gst, x0, ln, [&](auto S) {
          if constexpr (decltype(S)::v == SUMAT && !PS) {
            if (layer == 0) {
              float v[8];
              uint4 uu[5];
              mbar_wait(sb + BAR_STRIP, 0);
#pragma unroll
              for (int i = 0; i < 5; i++) uu[i] = lds4u(sb + OFF_CSB + w * 10240 + i * 2048 + t128 * 16);
#pragma unroll
              for (int z = 0; z < 4; z++) {
                v[2 * z] = v[2 * z + 1] = 0.f;
#pragma unroll
                for (int i = 0; i < 5; i++) { v[2 * z] += blo(word(uu[i], z)); v[2 * z + 1] += bhi(word(uu[i], z)); }
              }
              sts1u(sb + OFF_CSP + ((w * 4 + wi) * 32 + (lane & 3) * 8 + (lane >> 2)) * 4, __float_as_uint(strip_reduce(v, lane)));
              __syncwarp();
              mbar_arrive_if(sb + BAR_CSP, lane == 0);
            }
          }
          constexpr int i = decltype(S)::v - SIDE;
          if constexpr (i >= 0 && i < 10) {
            if (layer == 0) {
              const uint4 z = make_uint4(0, 0, 0, 0);
              if (i == 0) stg_strong(P.s->o + (u * 40 + (jj & 1) * 20 + 5 * (jj >> 1) + 4) * 128 + t128, z);
              if (i == 1) stg_strong(P.s->h + (u * 108 + (jj & 1) * 54 + 14 * (jj >> 1) + HPROBE) * 128 + t128, z);
              if (i >= 2 && i < 7) stg_strong(P.s->part + ((u * 8 + (jj ^ 1)) * 5 + i - 2) * 128 + t128, z);
              if (wi == 3) stg_strong(P.s->halo + (((i / 5) * 32 + u) * 8 + jj) * 160 + (i % 5) * 32 + lane, z);
            }
          }
        }, [&](auto C) {
          constexpr int ch = decltype(C)::v;
          if constexpr (ch == -1) {
#pragma unroll
            for (int z = 0; z < 5; z++) { ck[z] = ldcs(blk(1, 2 * z) / 2); cv[z] = ldcs(blk(2, 2 * z) / 2); }
          }
          if constexpr (ch == 0 || ch == 1) {
#pragma unroll
            for (int e = 0; e < 10; e++) {
              const int i = e >> 1, z = e & 1, bk = blk(1, e), bv = blk(2, e);
              const float kx = z ? ck[i].z : ck[i].x, ky = z ? ck[i].w : ck[i].y, vx = z ? cv[i].z : cv[i].x, vy = z ? cv[i].w : cv[i].y;
              if (ch == 0) {
                KH(e) = pack2(fmaf(kx, ln.nm1, acc[4 * bk + 2]) * ln.rs1, fmaf(ky, ln.nm1, acc[4 * bk + 3]) * ln.rs1);
                VH(e) = movm(pack2(fmaf(vx, ln.nm1, acc[4 * bv + 2]) * ln.rs1, fmaf(vy, ln.nm1, acc[4 * bv + 3]) * ln.rs1));
              } else {
                Kl[e] = pack2(fmaf(kx, ln.nm0, acc[4 * bk]), fmaf(ky, ln.nm0, acc[4 * bk + 1]));
                Vl[e] = movm(pack2(fmaf(vx, ln.nm0, acc[4 * bv]) * ln.rs0, fmaf(vy, ln.nm0, acc[4 * bv + 1]) * ln.rs0));
              }
            }
          }
          if constexpr (ch == 0) {
            uint4* const kvdst = opaque((wi == 3 ? hp : xs) + lane);
#pragma unroll
            for (int z = 0; z < 5; z++) { kvh[z].x |= wi == 3; st_strong(kvdst + z * 32, kvh[z]); }
            asm volatile("{.reg .u32 h; mov.u32 h, %%clock_hi; shr.u32 h, h, 31; lop3.b32 %0, h, %1, %0, 0xea;}" : "+f"(ln.nm0) : "r"(kvh[2].y));
#pragma unroll
            for (int z = 0; z < 5; z++) cq[z] = ldcs(blk(0, 2 * z) / 2);
          }
        });
        bar_sync(1 + w, 128);
        STAMP(w, 2 + 8 * hl);
#pragma unroll
        for (int e = 0; e < 10; e++) {
          const int b = blk(0, e);
          const float cx = (e & 1) ? cq[e >> 1].z : cq[e >> 1].x, cy = (e & 1) ? cq[e >> 1].w : cq[e >> 1].y;
          Ql[e] = pack2(fmaf(cx, ln.nm0, acc[4 * b]), fmaf(cy, ln.nm0, acc[4 * b + 1]));
          Qh[e] = pack2(fmaf(cx, ln.nm1, acc[4 * b + 2]), fmaf(cy, ln.nm1, acc[4 * b + 3]));
        }
        uint32_t lz;
        asm volatile("{.reg .u32 h; mov.u32 h, %%clock_hi; shr.u32 h, h, 31; lop3.b32 %0, h, %1, %2, 0xea;}" : "=r"(lz) : "r"(Vl[9] ^ Qh[9]), "r"(lane));
        const uint4* const kvsrc = opaque((wi > 0 ? xs - 160 : m > 0 ? hp - 2 * 8 * 160 : xs) + lz);
#pragma unroll
        for (int i = 0; i < 5; i++) kvp[i] = ld_strong(kvsrc + i * 32);
        const bool p0 = 2 * t > g, p1 = 2 * t + 1 > g;
        constexpr float SC = 0.22360679774997896f * 1.4426950408889634f;
        const float rb0 = __shfl_sync(~0u, ln.rs0, 8 * t), rb1 = __shfl_sync(~0u, ln.rs0, 8 * t + 4);
        const float cq0 = SC * ln.rs0, cq1 = SC * ln.rs1;
        const bool noprev = wi == 0 && m == 0;
        const float cp = noprev ? 0.f : cq0, bias = noprev ? -1.4426950408889634e9f : 0.f;
        const float cf[4] = {p0 ? cp : cq0 * rb0, p1 ? cp : cq0 * rb1, p0 ? cq1 * rb0 : cq1, p1 ? cq1 * rb1 : cq1};
        const float bs0 = p0 ? bias : 0.f, bs1 = p1 ? bias : 0.f;
        float lg[4][4];
        uint32_t qs[4][2];
#pragma unroll
        for (int h = 0; h < 4; h++) {
          const int e0 = 5 * (h >> 1) + ((h & 1) ? 3 : 0), e1 = e0 + 1, es = 5 * (h >> 1) + 2;
          const bool mine = (h & 1) ? (t >= 2) : (t < 2);
          qs[h][0] = mine ? Ql[es] : 0u; qs[h][1] = mine ? Qh[es] : 0u;
          float sb_[4] = {0.f, 0.f, 0.f, 0.f}, sc[4] = {0.f, 0.f, 0.f, 0.f};
          mma16816(sb_, Ql[e0], Qh[e0], Ql[e1], Qh[e1], Kl[e0], Kl[e1]); mma1688(sb_, qs[h][0], qs[h][1], Kl[es]);
          mma16816(sc, Ql[e0], Qh[e0], Ql[e1], Qh[e1], KH(e0), KH(e1)); mma1688(sc, qs[h][0], qs[h][1], KH(es));
          lg[h][0] = sb_[0]; lg[h][1] = sb_[1]; lg[h][2] = (p0 ? sb_[2] : sc[2]) * cf[2]; lg[h][3] = (p1 ? sb_[3] : sc[3]) * cf[3];
        }
        STAMP(w, 3 + 8 * hl);
        uint4* const go = opaque(P.s->o + (u * 40 + (jj & 1) * 20) * 128 + t128);
        uint4* const god = pinned(go + 5 * (jj >> 1) * 128);
        {
          uint32_t need;
          asm volatile("{.reg .u32 h; mov.u32 h, %%clock_hi; shr.u32 h, h, 31; xor.b32 %0, h, %1;}" : "=r"(need) : "r"((uint32_t)(wi == 0 && m > 0)));
          while (true) {
            uint32_t ok;
            asm("lop3.b32 %0, %1, %2, %3, 0x80;" : "=r"(ok) : "r"(kvp[0].x), "r"(kvp[1].x), "r"(need));
            asm("lop3.b32 %0, %0, %1, %2, 0x80;" : "+r"(ok) : "r"(kvp[2].x), "r"(kvp[3].x));
            if (!__any_sync(~0u, (ok & kvp[4].x) != need)) break;
#pragma unroll
            for (int i = 0; i < 5; i++) kvp[i] = ld_strong(kvsrc + i * 32);
          }
        }
        STAMP(w, 4 + 8 * hl);
        float mx[4][2];
#pragma unroll
        for (int h = 0; h < 4; h++) {
          const int e0 = 5 * (h >> 1) + ((h & 1) ? 3 : 0), e1 = e0 + 1, es = 5 * (h >> 1) + 2;
          float sa[4] = {0.f, 0.f, 0.f, 0.f};
          mma16816(sa, Ql[e0], Qh[e0], Ql[e1], Qh[e1], KP(e0), KP(e1)); mma1688(sa, qs[h][0], qs[h][1], KP(es));
          lg[h][0] = fmaf(p0 ? sa[0] : lg[h][0], cf[0], bs0); lg[h][1] = fmaf(p1 ? sa[1] : lg[h][1], cf[1], bs1);
          mx[h][0] = fmaxf(lg[h][0], lg[h][1]); mx[h][1] = fmaxf(lg[h][2], lg[h][3]);
        }
#pragma unroll
        for (int o_ = 1; o_ <= 2; o_++)
#pragma unroll
          for (int h = 0; h < 4; h++) { mx[h][0] = fmaxf(mx[h][0], __shfl_xor_sync(~0u, mx[h][0], o_)); mx[h][1] = fmaxf(mx[h][1], __shfl_xor_sync(~0u, mx[h][1], o_)); }
#pragma unroll
        for (int h = 0; h < 4; h++) {
#pragma unroll
          for (int i = 0; i < 4; i++) lg[h][i] = ex2(lg[h][i] - mx[h][i >> 1]);
          mx[h][0] = lg[h][0] + lg[h][1]; mx[h][1] = lg[h][2] + lg[h][3];
        }
#pragma unroll
        for (int o_ = 1; o_ <= 2; o_++)
#pragma unroll
          for (int h = 0; h < 4; h++) { mx[h][0] += __shfl_xor_sync(~0u, mx[h][0], o_); mx[h][1] += __shfl_xor_sync(~0u, mx[h][1], o_); }
        STAMP(w, 68 + 8 * hl);
        uint4 o[5];
        const uint32_t mk = (p0 ? 0xffffu : 0u) | (p1 ? 0xffff0000u : 0u);
#pragma unroll
        for (int h = 0; h < 4; h++) {
          const int e0 = 5 * (h >> 1) + ((h & 1) ? 3 : 0), e1 = e0 + 1, es = 5 * (h >> 1) + 2;
          const float rl = rcp(mx[h][0]), rh = rcp(mx[h][1]);
          const uint32_t pl = pack2(lg[h][0] * rl, lg[h][1] * rl), ph = pack2(lg[h][2] * rh, lg[h][3] * rh);
          const uint32_t pa = pl & mk, pbl = pl & ~mk, pbh = ph & mk, pc = ph & ~mk;
#pragma unroll
          for (int z = 0; z < 3; z++) {
            const int e = z == 0 ? e0 : z == 1 ? e1 : es;
            float oc[4] = {0.f, 0.f, 0.f, 0.f};
            mma16816(oc, pa, 0u, pbl, pbh, VP(e), Vl[e]); mma1688(oc, 0u, pc, VH(e));
            const uint32_t ol = pack2(oc[0], oc[1]), oh = pack2(oc[2], oc[3]);
            if (z < 2 || !(h & 1) || t >= 2) { word(o[e >> 1], 2 * (e & 1)) = ol; word(o[e >> 1], 2 * (e & 1) + 1) = oh; }
          }
        }
#pragma unroll
        for (int i = 0; i < 5; i++) { o[i].x = tagged(o[i].x, layer ^ 1); stg_strong(god + i * 128, o[i]); }
        STAMP(w, 5 + 8 * hl);
        mainloop<1>(acc2, o, go, layer ^ 1, c, gst, x0, ln, [](auto) {}, send);
      } else {
        float acc[112];
        uint4 h[14];
        uint4* const gh = P.s->h + (u * 108 + (jj & 1) * 54) * 128 + t128;
        const uint32_t htag = layer ^ 1;
        float4 ch_[14];
        auto hpiece = [&](int i) {
          const float4 cs = ch_[i];
          h[i].x = tagged(pack2_relu(fmaf(cs.x, ln.nm0, acc[8 * i]), fmaf(cs.y, ln.nm0, acc[8 * i + 1])), htag);
          h[i].y = pack2_relu(fmaf(cs.x, ln.nm1, acc[8 * i + 2]), fmaf(cs.y, ln.nm1, acc[8 * i + 3]));
          h[i].z = pack2_relu(fmaf(cs.z, ln.nm0, acc[8 * i + 4]), fmaf(cs.w, ln.nm0, acc[8 * i + 5]));
          h[i].w = pack2_relu(fmaf(cs.z, ln.nm1, acc[8 * i + 6]), fmaf(cs.w, ln.nm1, acc[8 * i + 7]));
        };
        uint4* ghd;
        auto hsend = [&](int i) { if (i < 12) stg_strong(ghd + i * 128, h[i]); else stg_strong_if(ghd + i * 128, h[i], jj < 6); };
        mainloop<2>(acc, xr, gx, 0, c, gst, x0, ln, [&](auto S) {
          if (decltype(S)::v == SIDE && wi == 0 && m > 0) {
#pragma unroll
            for (int i = 0; i < 5; i++) stg_strong(P.s->halo + ((layer * 32 + u - 2) * 8 + jj) * 160 + i * 32 + lane, make_uint4(0, 0, 0, 0));
          }
        }, [&](auto C) {
          constexpr int i = decltype(C)::v;
          if constexpr (i == -1) ghd = opaque(gh + 14 * (jj >> 1) * 128);
          if constexpr (i + 1 < 8) ch_[i + 1] = ldcs(16 + i + 1);
          if constexpr (i >= 0 && i < 8) { hpiece(i); hsend(i); }
          if constexpr (i == 9) {
#pragma unroll
            for (int z = 8; z < 14; z++) ch_[z] = ldcs(16 + z);
          }
        });
        STAMP(w, 2 + 8 * hl);
        os0 = ln.rs0; os1 = ln.rs1;
#pragma unroll
        for (int i = 8; i < 14; i++) { hpiece(i); hsend(i); }
        STAMP(w, 5 + 8 * hl);
        mainloop<3>(acc2, h, gh, htag, c, gst, x0, ln, [](auto) {}, send);
      }
      {
        STAMP(w, 6 + 8 * hl);
        float k[40];
#pragma unroll
        for (int i = 0; i < 40; i++) k[i] = fmaf(acc2[i < 32 ? 48 + i : i - 32], (i & 2) ? os1 : os0, rz[i]);
        STAMP(w, 64 + 8 * hl);
        uint32_t tz;
        asm volatile("{.reg .u32 h; mov.u32 h, %%clock_hi; shr.u32 h, h, 31; lop3.b32 h, h, %2, %3, 0x80; lop3.b32 h, h, %4, %5, 0x80; xor.b32 %0, h, %1;}"
                     : "=r"(tz) : "r"(ptag), "f"(k[9]), "f"(k[19]), "f"(k[29]), "f"(k[39]));
        while (true) {
          if (!stale<5>(pv, tz, 1)) break;
#pragma unroll
          for (int i = 0; i < 5; i++) pv[i] = ldg_strong(gp + i * 128);
        }
        STAMP(w, 7 + 8 * hl);
        const uint32_t more = hl < 3;
        mbar_arrive_if(sb + BAR_DONE, (lane | more) == 0);
#pragma unroll
        for (int i = 0; i < 5; i++) {
#pragma unroll
          for (int z = 0; z < 4; z++) {
            const uint32_t r = word(pv[i], z);
            const float sc = (z & 1) ? os1 : os0;
            word(xr[i], z) = pack2(fmaf(blo(r), sc, k[8 * i + 2 * z]), fmaf(bhi(r), sc, k[8 * i + 2 * z + 1]));
          }
          x0[i] = xr[i].x;
          asm("lop3.b32 %0, %1, %2, %3, 0xb8;" : "=r"(xr[i].x) : "r"(x0[i]), "r"(more), "r"(hl));
          stg_strong_if(i < 4 ? gxa + i * 128 : gxb, xr[i], more);
        }
        if (hl == 3) {
          const uint32_t row = lbase + (lane & 15) * 160 + (lane >> 4) * 16;
          __syncwarp();
#pragma unroll
          for (int i = 0; i < 5; i++) stsm4(row + (i < 4 ? (i + (jj & 1)) * 32 : (jj & 1) ? 0 : 128), xr[i]);
          asm volatile("fence.proxy.async.shared::cta;" ::: "memory");
          __syncwarp();
          if (elect()) {
            asm volatile("cp.async.bulk.tensor.3d.global.shared::cta.bulk_group [%0, {%2,%3,%4}], [%1];"
                         ::"l"(&M.to), "r"(lbase), "r"(80 * jj), "r"(w), "r"(64 * m + 16 * wi) : "memory");
            asm volatile("cp.async.bulk.commit_group;" ::: "memory");
            asm volatile("cp.async.bulk.wait_group.read 0;" ::: "memory");
          }
          __syncwarp();
        }
        STAMP(w, 8 + 8 * hl);
        if (warp == 0) GSTAMP(2 + hl);
      }
    }
  }
}

typedef CUresult (*EncFn)(CUtensorMap*, CUtensorMapDataType, cuuint32_t, void*, const cuuint64_t*, const cuuint64_t*, const cuuint32_t*,
                          const cuuint32_t*, CUtensorMapInterleave, CUtensorMapSwizzle, CUtensorMapL2promotion, CUtensorMapFloatOOBfill);

void make4d(EncFn enc, CUtensorMap* mp, const void* p, uint64_t K, uint64_t N, uint32_t atoms, uint32_t steps) {
  cuuint64_t d[4] = {32, 16, N / 32, K / 16}, s[3] = {N * 2, 64, N * 32};
  cuuint32_t b[4] = {32, 16, atoms, steps}, e[4] = {1, 1, 1, 1};
  enc(mp, CU_TENSOR_MAP_DATA_TYPE_BFLOAT16, 4, (void*)p, d, s, b, e, CU_TENSOR_MAP_INTERLEAVE_NONE, CU_TENSOR_MAP_SWIZZLE_64B,
      CU_TENSOR_MAP_L2_PROMOTION_L2_128B, CU_TENSOR_MAP_FLOAT_OOB_FILL_NONE);
}

}

extern "C" void kernel_launch(void* const* d_in, const int* in_sizes, int n_in, void* d_out, int out_size) {
  (void)in_sizes; (void)n_in; (void)out_size;
  static EncFn enc = nullptr;
  static Scratch* scratch = nullptr;
  if (!enc) {
    void* f = nullptr; cudaDriverEntryPointQueryResult q;
    cudaGetDriverEntryPoint("cuTensorMapEncodeTiled", &f, cudaEnableDefault, &q);
    enc = (EncFn)f;
    cudaGetSymbolAddress((void**)&scratch, gS);
    cudaFuncSetAttribute(mega_kernel, cudaFuncAttributeMaxDynamicSharedMemorySize, SMEM_BYTES);
  }
  Ptrs P; Maps M;
  P.x = (const __nv_bfloat16*)d_in[0]; P.wqkv = (const __nv_bfloat16*)d_in[1]; M.wo = (const __nv_bfloat16*)d_in[2];
  P.w1 = (const __nv_bfloat16*)d_in[4]; P.w2 = (const __nv_bfloat16*)d_in[5]; P.out = (__nv_bfloat16*)d_out; P.s = scratch;
  for (int i = 0; i < 4; i++) {
    const cuuint64_t d[4] = {640, 16, 3, 40}, st[3] = {3840, 1280, 16 * 3840};
    const cuuint32_t b[4] = {i < 2 ? 64u : 16u, 16, 3, 1u + (i & 1)}, e[4] = {1, 1, 1, 1};
    enc(&M.tw[i], CU_TENSOR_MAP_DATA_TYPE_BFLOAT16, 4, (void*)P.wqkv, d, st, b, e, CU_TENSOR_MAP_INTERLEAVE_NONE,
        i < 2 ? CU_TENSOR_MAP_SWIZZLE_128B : CU_TENSOR_MAP_SWIZZLE_32B, CU_TENSOR_MAP_L2_PROMOTION_L2_128B, CU_TENSOR_MAP_FLOAT_OOB_FILL_NONE);
  }
  for (int i = 0; i < 2; i++) {
    const cuuint64_t d[3] = {640, 2, 1024}, st[2] = {1280, 2560};
    const cuuint32_t b[3] = {80, 1, i ? 16u : 64u}, e[3] = {1, 1, 1};
    enc(i ? &M.to : &M.tx, CU_TENSOR_MAP_DATA_TYPE_BFLOAT16, 3, i ? d_out : (void*)P.x, d, st, b, e, CU_TENSOR_MAP_INTERLEAVE_NONE, CU_TENSOR_MAP_SWIZZLE_NONE,
        CU_TENSOR_MAP_L2_PROMOTION_L2_128B, CU_TENSOR_MAP_FLOAT_OOB_FILL_NONE);
  }
  for (int i = 0; i < 2; i++) {
    const cuuint64_t N = i ? 1728 : 1920, d[2] = {N, 640}, st[1] = {N * 2};
    const cuuint32_t b[2] = {32, 160}, e[2] = {1, 1};
    enc(&M.tc[i], CU_TENSOR_MAP_DATA_TYPE_BFLOAT16, 2, (void*)(i ? P.w1 : P.wqkv), d, st, b, e, CU_TENSOR_MAP_INTERLEAVE_NONE,
        CU_TENSOR_MAP_SWIZZLE_NONE, CU_TENSOR_MAP_L2_PROMOTION_L2_128B, CU_TENSOR_MAP_FLOAT_OOB_FILL_NONE);
  }
  for (int n = 1; n <= 3; n++) {
    make4d(enc, &M.tw[3 + n], M.wo, 640, 640, 5, n);
    if (n < 3) make4d(enc, &M.tw[6 + n], P.w1, 640, 1728, 7, n);
    make4d(enc, &M.tw[8 + n], P.w2, 1728, 640, 5, n);
  }
  mega_kernel<<<NCTA, 384, SMEM_BYTES>>>(P, M);
}
```
